```python
import torch

def _softmax(x, axis=-1):
    return torch.softmax(x, dim=axis)
def _gelu(x):
    return torch.nn.functional.gelu(x, approximate="tanh")
def _silu(x):
    return torch.nn.functional.silu(x)
def _sigmoid(x):
    return torch.sigmoid(x)
def _layernorm(x, axis=-1, eps=1e-5):
    m = x.mean(dim=axis, keepdim=True)
    v = x.var(dim=axis, keepdim=True, unbiased=False)
    return (x - m) / torch.sqrt(v + eps)
def _scatter_add(tgt, idx, src, axis=0):
    return tgt.clone().index_add_(axis, idx, src)
def _segment_sum(src, seg, n):
    out = torch.zeros((n,) + src.shape[1:], dtype=src.dtype)
    return out.index_add_(0, seg, src)
def _pad(x, pw):
    flat = tuple(v for pair in reversed(pw) for v in pair)
    return torch.nn.functional.pad(x, flat)

kernel_name = 'sequential_preLN__ssm_conv_s4__glu_gated_reglu__prompt'

def setup_inputs():

    _w = (lambda a: (lambda t: t.to(torch.bfloat16) if t.is_floating_point() else t)(torch.as_tensor(a)))
    def _A_setup():
        B, L, D, N = 1, 2048, 576, 128
        A_re = -(lambda _x: torch.exp(torch.as_tensor(_x)))((lambda *s: torch.randn(*s, dtype=torch.bfloat16) * 6.4)(D, N))
        A_im = torch.pi * (lambda *s: torch.randn(*s, dtype=torch.bfloat16) * 0.05)(D, N)
        B_re = (lambda *s: torch.randn(*s, dtype=torch.bfloat16) * 0.05)(D, N)
        B_im = (lambda *s: torch.randn(*s, dtype=torch.bfloat16) * 0.05)(D, N)
        C_re = (lambda *s: torch.randn(*s, dtype=torch.bfloat16) * 0.05)(D, N)
        C_im = (lambda *s: torch.randn(*s, dtype=torch.bfloat16) * 0.05)(D, N)
        log_dt = (lambda *s: torch.randn(*s, dtype=torch.bfloat16) * 0.05)(D) * 0.5 - 4.0
        Dskip = (lambda *s: torch.randn(*s, dtype=torch.bfloat16) * 0.05)(D)
        return {
            "u": _w((lambda *s: torch.randn(*s, dtype=torch.bfloat16) * 0.05)(B, L, D)),
            "A_re": _w(A_re),
            "A_im": _w(A_im),
            "B_re": _w(B_re),
            "B_im": _w(B_im),
            "C_re": _w(C_re),
            "C_im": _w(C_im),
            "log_dt": _w(log_dt),
            "Dskip": _w(Dskip),
        }
    _A_in = _A_setup()

    def _B_setup():
        B, S, D, F = 1, 2048, 576, 4608
        return {
            "x": _w((lambda *s: torch.randn(*s, dtype=torch.bfloat16) * 0.05)(B, S, D)),
            "W_gate": _w((lambda *s: torch.randn(*s, dtype=torch.bfloat16) * 0.4)(D, F) * (2.0 / D) ** 0.5),
            "W_up": _w((lambda *s: torch.randn(*s, dtype=torch.bfloat16) * 0.4)(D, F) * (2.0 / D) ** 0.5),
            "W_down": _w((lambda *s: torch.randn(*s, dtype=torch.bfloat16) * 0.4)(F, D) * (1.0 / F) ** 0.5),
        }
    _B_in = _B_setup()

    return {
        "A_u": _A_in["u"],
        "A_A_re": _A_in["A_re"],
        "A_A_im": _A_in["A_im"],
        "A_B_re": _A_in["B_re"],
        "A_B_im": _A_in["B_im"],
        "A_C_re": _A_in["C_re"],
        "A_C_im": _A_in["C_im"],
        "A_log_dt": _A_in["log_dt"],
        "A_Dskip": _A_in["Dskip"],
        "B_x": _B_in["x"],
        "B_W_gate": _B_in["W_gate"],
        "B_W_up": _B_in["W_up"],
        "B_W_down": _B_in["W_down"],
    }

def reference(A_u, A_A_re, A_A_im, A_B_re, A_B_im, A_C_re, A_C_im, A_log_dt, A_Dskip, B_x, B_W_gate, B_W_up, B_W_down):
    def _A_ref(u, A_re, A_im, B_re, B_im, C_re, C_im, log_dt, Dskip):
        Bsz, L, D = u.shape
        dt = torch.exp(log_dt)[:, None]
        A = A_re + 1j * A_im
        Bc = B_re + 1j * B_im
        Cc = C_re + 1j * C_im
        logdA = dt * A
        dB = dt * Bc
        l = (lambda x, dt: x.to(dt))(torch.arange(L), A_re.dtype)
        P = torch.exp(logdA[:, :, None] * l[None, None, :])
        K = torch.einsum("dn,dnl,dn->dl", Cc, P, dB).real
        L2 = 2 * L
        Kp = _pad(K, ((0, 0), (0, L)))
        up = (lambda x, *d: x.permute(*d))(u, 0, 2, 1)
        up = _pad(up, ((0, 0), (0, 0), (0, L)))
        Kf = (lambda x, axes=(-2,-1): torch.fft.rfft2(x.float(), dim=axes))(Kp[:, None, :], axes=(-2, -1))
        Uf = (lambda x, axes=(-2,-1): torch.fft.rfft2(x.float(), dim=axes))(up[:, :, None, :], axes=(-2, -1))
        Yf = Uf * Kf[None, :, :, :]
        y = (lambda x, s, axes=(-2,-1): torch.fft.irfft2(x, s=s, dim=axes).to(torch.bfloat16))(Yf, (1, L2), axes=(-2, -1))[:, :, 0, :L]
        y = (lambda x, *d: x.permute(*d))(y, 0, 2, 1) + u * Dskip[None, None, :]
        return y

    def _B_ref(x, W_gate, W_up, W_down):
        gate = torch.einsum("bsd,df->bsf", x, W_gate)
        up = torch.einsum("bsd,df->bsf", x, W_up)
        gate = gate * (lambda x, dt: x.to(dt))(gate > 0, gate.dtype)
        h = gate * up
        return torch.einsum("bsf,fd->bsd", h, W_down)

    x = A_u
    h = x + _A_ref(_layernorm(x, axis=-1), A_A_re, A_A_im, A_B_re, A_B_im, A_C_re, A_C_im, A_log_dt, A_Dskip)
    h2 = h + _B_ref(_layernorm(h, axis=-1), B_W_gate, B_W_up, B_W_down)
    return h2
```

```cpp
#include <cuda_runtime.h>
#include <cuda_bf16.h>
#include <cuda.h>
#include <stdint.h>

constexpr int L_SEQ = 2048, D_MODEL = 576, N_STATE = 128, F_FFN = 4608;
constexpr int NCTA = 128;
constexpr int NTHREADS = 384;

#define KS1 3
constexpr int KS2 = 2 * KS1;
constexpr int NST1 = 36 / KS1;
constexpr int NST2 = 36 / KS2;
constexpr int STAGE_BYTES = KS1 * 16 * 128 * 2;
constexpr int RING_BYTES = 98304;
constexpr int NSTAGE = RING_BYTES / STAGE_BYTES;
constexpr int SM_PARK = 0;
constexpr int SM_RING = 131072;
constexpr int SM_BAR = SM_RING + RING_BYTES;
constexpr int SMEM_BYTES = SM_BAR + 2048;
constexpr int HBOX8_OFF = SM_RING + RING_BYTES - 16384;
constexpr int HBOX8_STAGE = (RING_BYTES - 16384) / STAGE_BYTES;

#define EARLY HBOX8_STAGE
#define REL_K 0
#define G2 2
constexpr int C_U = 0;
constexpr int C_X = 5120;
constexpr int C_R2 = 9216;
constexpr int C_G0 = C_R2 + 6400;
constexpr int C_G1 = C_G0 + 2176;
constexpr int C_PE = C_R2 + 10752;
constexpr int C_PO = C_PE + 1344;
constexpr int C_T2 = C_PO + 1280;
constexpr int C_T3 = C_T2 + 768;
constexpr int C_MISC = C_T3 + 512;
constexpr int C_Y0 = 24064;
constexpr int C_Y1 = C_Y0 + 4096;
constexpr int C_YF = C_Y1 + 4096;
constexpr int C_Y3 = C_YF + 3072;
constexpr int CHS = 37888;
static_assert(C_MISC + 16 <= C_Y0 && C_Y0 % 512 == 0 && C_Y3 + 2048 <= CHS, "smem map");
constexpr int LN_PITCH = 1168;
constexpr int SM_LN = 5 * CHS;
constexpr int LN_STAT = 16 * LN_PITCH + 64;
constexpr int LN_TILE = LN_STAT + 1024;
constexpr int SM_STAT = SM_LN + LN_TILE;
static_assert(CHS % 1024 == 0 && SM_STAT % 16 == 0 && SM_STAT + 12288 <= SM_BAR, "smem map");

#define KG_UNROLL_N 2
constexpr int KG_UNROLL = KG_UNROLL_N;
#define PF_STRIDE 128
#define NEAR_BS 9
constexpr int B_FULL = 0;
constexpr int B_EMPTY = B_FULL + NSTAGE;
constexpr int B_HFULL = B_EMPTY + NSTAGE;
constexpr int B_HFREE = B_HFULL + 18;
constexpr int B_STFULL = B_HFREE + 1;
constexpr int B_C8 = B_STFULL + 16;
constexpr int B_XS = B_C8 + 1;
constexpr int B_COUNT = B_XS + 1;

__device__ __align__(1024) __nv_bfloat16 g_hT[D_MODEL * L_SEQ];
__device__ __align__(1024) uint4 g_part[16 * 9 * 8 * 1024];
__device__ unsigned int g_flag[16 * 9 * 8 * 2];
__device__ unsigned int g_ticket[4];
__device__ unsigned int g_epoch;
__device__ __align__(1024) uint4 g_xT[D_MODEL * 256];
__device__ __align__(128) uint4 g_stat[768];
__device__ unsigned int g_done[96];
#define HAVE_HT
#define TS(k, cond)
#define TS_INIT()
#define TS_DUMP()

#define SUB(k)
__device__ __forceinline__ uint32_t smem_u32(const void* p) { return (uint32_t)__cvta_generic_to_shared(p); }
__device__ __forceinline__ void mbar_init(uint32_t bar, int cnt) { asm volatile("mbarrier.init.shared::cta.b64 [%0], %1;" ::"r"(bar), "r"(cnt)); }
__device__ __forceinline__ void mbar_expect_tx(uint32_t bar, uint32_t bytes) { asm volatile("mbarrier.arrive.expect_tx.shared::cta.b64 _, [%0], %1;" ::"r"(bar), "r"(bytes) : "memory"); }
__device__ __forceinline__ void mbar_arrive(uint32_t bar) { asm volatile("mbarrier.arrive.shared::cta.b64 _, [%0];" ::"r"(bar) : "memory"); }
__device__ __forceinline__ void mbar_wait(uint32_t bar, uint32_t parity) {
  asm volatile(
      "{\n.reg .pred p, q;\n.reg .u32 it;\n"
      "mov.u32 it, 0;\n"
      "MW_LOOP_%=:\n"
      "mbarrier.try_wait.parity.shared::cta.b64 p, [%0], %1;\n"
      "@p bra MW_DONE_%=;\n"
      "add.u32 it, it, 1;\n"
      "setp.gt.u32 q, it, 4194304;\n"
      "@q trap;\n"
      "bra MW_LOOP_%=;\n"
      "MW_DONE_%=:\n}\n" ::"r"(bar), "r"(parity) : "memory");
}
__device__ __forceinline__ void tma_load_2d(uint32_t dst, const CUtensorMap* tm, int c0, int c1, uint32_t bar) {
  asm volatile("cp.async.bulk.tensor.2d.shared::cluster.global.mbarrier::complete_tx::bytes [%0], [%1, {%3, %4}], [%2];"
               ::"r"(dst), "l"(tm), "r"(bar), "r"(c0), "r"(c1) : "memory");
}
__device__ __forceinline__ void bulk_store(void* dst, uint32_t src, uint32_t bytes) {
  asm volatile("cp.async.bulk.global.shared::cta.bulk_group [%0], [%1], %2;" ::"l"(dst), "r"(src), "r"(bytes) : "memory");
}
__device__ __forceinline__ void bulk_load(uint32_t dst, const void* src, uint32_t bytes, uint32_t bar) {
  asm volatile("cp.async.bulk.shared::cluster.global.mbarrier::complete_tx::bytes [%0], [%1], %2, [%3];" ::"r"(dst), "l"(src), "r"(bytes), "r"(bar) : "memory");
}
__device__ __forceinline__ void bulk_commit() { asm volatile("cp.async.bulk.commit_group;" ::: "memory"); }
__device__ __forceinline__ void bulk_wait0() { asm volatile("cp.async.bulk.wait_group 0;" ::: "memory"); }
__device__ __forceinline__ void fence_async_smem() { asm volatile("fence.proxy.async.shared::cta;" ::: "memory"); }
__device__ __forceinline__ void fence_async_global() { asm volatile("fence.proxy.async.global;" ::: "memory"); }
__device__ __forceinline__ void wg_fence() { asm volatile("wgmma.fence.sync.aligned;" ::: "memory"); }
__device__ __forceinline__ void wg_commit() { asm volatile("wgmma.commit_group.sync.aligned;" ::: "memory"); }
template <int N> __device__ __forceinline__ void wg_wait() { asm volatile("wgmma.wait_group.sync.aligned %0;" ::"n"(N) : "memory"); }
template <int N> __device__ __forceinline__ void reg_fence(float* d) {
#pragma unroll
  for (int i = 0; i < N; i++) asm volatile("" : "+f"(d[i])::"memory");
}
__device__ __forceinline__ uint64_t mkdesc(uint32_t addr, uint32_t lbo, uint32_t sbo, uint32_t swz) {
  return (uint64_t)((addr & 0x3FFFF) >> 4) | ((uint64_t)(lbo >> 4) << 16) | ((uint64_t)(sbo >> 4) << 32) | ((uint64_t)swz << 62);
}
__device__ __forceinline__ void ldsm4_t(uint32_t addr, uint32_t& r0, uint32_t& r1, uint32_t& r2, uint32_t& r3) {
  asm volatile("ldmatrix.sync.aligned.m8n8.x4.trans.shared.b16 {%0,%1,%2,%3}, [%4];" : "=r"(r0), "=r"(r1), "=r"(r2), "=r"(r3) : "r"(addr) : "memory");
}
__device__ __forceinline__ void ldsm4(uint32_t addr, uint32_t& r0, uint32_t& r1, uint32_t& r2, uint32_t& r3) {
  asm volatile("ldmatrix.sync.aligned.m8n8.x4.shared.b16 {%0,%1,%2,%3}, [%4];" : "=r"(r0), "=r"(r1), "=r"(r2), "=r"(r3) : "r"(addr) : "memory");
}
__device__ __forceinline__ void mma_bf16(float* c, uint32_t a0, uint32_t a1, uint32_t a2, uint32_t a3, uint32_t b0, uint32_t b1) {
  asm volatile("mma.sync.aligned.m16n8k16.row.col.f32.bf16.bf16.f32 {%0,%1,%2,%3}, {%4,%5,%6,%7}, {%8,%9}, {%0,%1,%2,%3};"
               : "+f"(c[0]), "+f"(c[1]), "+f"(c[2]), "+f"(c[3]) : "r"(a0), "r"(a1), "r"(a2), "r"(a3), "r"(b0), "r"(b1));
}
__device__ __forceinline__ uint32_t pack_bf16(float lo, float hi) {
  uint32_t r; asm("cvt.rn.bf16x2.f32 %0, %1, %2;" : "=r"(r) : "f"(hi), "f"(lo)); return r;
}
__device__ __forceinline__ float bf_lo(uint32_t v) { return __uint_as_float(v << 16); }
__device__ __forceinline__ float bf_hi(uint32_t v) { return __uint_as_float(v & 0xFFFF0000u); }
__device__ __forceinline__ float rbf(float x) { return __bfloat162float(__float2bfloat16(x)); }
__device__ __forceinline__ uint32_t sub_bf16x2(uint32_t a, uint32_t b) {
  uint32_t r; asm("sub.rn.bf16x2 %0, %1, %2;" : "=r"(r) : "r"(a), "r"(b)); return r;
}
__device__ __forceinline__ void sts128(uint32_t addr, uint32_t a, uint32_t b, uint32_t c, uint32_t d) {
  asm volatile("st.shared.v4.b32 [%0], {%1,%2,%3,%4};" ::"r"(addr), "r"(a), "r"(b), "r"(c), "r"(d) : "memory");
}
__device__ __forceinline__ void lds128(uint32_t addr, uint32_t& a, uint32_t& b, uint32_t& c, uint32_t& d) {
  asm volatile("ld.shared.v4.b32 {%0,%1,%2,%3}, [%4];" : "=r"(a), "=r"(b), "=r"(c), "=r"(d) : "r"(addr) : "memory");
}
__device__ __forceinline__ unsigned ld_acquire(const unsigned* p) {
  unsigned v; asm volatile("ld.acquire.gpu.global.u32 %0, [%1];" : "=r"(v) : "l"(p) : "memory"); return v;
}
__device__ __forceinline__ void st_release(unsigned* p, unsigned v) {
  asm volatile("st.release.gpu.global.u32 [%0], %1;" ::"l"(p), "r"(v) : "memory");
}
__device__ __forceinline__ void wait_flag(const unsigned* p, unsigned epoch) {
  asm volatile(
      "{\n.reg .pred p, q;\n.reg .u32 it, v;\n.reg .s32 d;\n"
      "mov.u32 it, 0;\n"
      "WF_LOOP_%=:\n"
      "ld.acquire.gpu.global.u32 v, [%0];\n"
      "sub.s32 d, v, %1;\n"
      "setp.ge.s32 p, d, 0;\n"
      "@p bra WF_DONE_%=;\n"
      "add.u32 it, it, 1;\n"
      "setp.gt.u32 q, it, 4194304;\n"
      "@q trap;\n"
      "bra WF_LOOP_%=;\n"
      "WF_DONE_%=:\n}\n" ::"l"(p), "r"(epoch) : "memory");
}
__device__ __forceinline__ void wait_flag4(const unsigned* p, unsigned epoch) {
  asm volatile(
      "{\n.reg .pred p, q;\n.reg .u32 it, v0, v1, v2, v3;\n"
      "mov.u32 it, 0;\n"
      "W4_LOOP_%=:\n"
      "ld.acquire.gpu.global.v4.u32 {v0, v1, v2, v3}, [%0];\n"
      "setp.eq.u32 p, v0, %1;\n"
      "setp.eq.and.u32 p, v1, %1, p;\n"
      "setp.eq.and.u32 p, v2, %1, p;\n"
      "setp.eq.and.u32 p, v3, %1, p;\n"
      "@p bra W4_DONE_%=;\n"
      "add.u32 it, it, 1;\n"
      "setp.gt.u32 q, it, 4194304;\n"
      "@q trap;\n"
      "bra W4_LOOP_%=;\n"
      "W4_DONE_%=:\n}\n" ::"l"(p), "r"(epoch) : "memory");
}
__device__ __forceinline__ uint4 ldg_cg(const uint4* p) {
  uint4 v; asm volatile("ld.global.cg.v4.u32 {%0,%1,%2,%3}, [%4];" : "=r"(v.x), "=r"(v.y), "=r"(v.z), "=r"(v.w) : "l"(p) : "memory"); return v;
}
#define named_bar(id, n) asm volatile("bar.sync %0, %1;" ::"n"(id), "n"(n) : "memory")

__device__ __forceinline__ void wg_bar(int wgi) { asm volatile("bar.sync %0, 128;" ::"r"(wgi + 1) : "memory"); }
__device__ __forceinline__ void stsm4(uint32_t addr, uint32_t r0, uint32_t r1, uint32_t r2, uint32_t r3) {
  asm volatile("stmatrix.sync.aligned.m8n8.x4.shared.b16 [%0], {%1,%2,%3,%4};" ::"r"(addr), "r"(r0), "r"(r1), "r"(r2), "r"(r3) : "memory");
}
__device__ __forceinline__ void stsm4_t(uint32_t addr, uint32_t r0, uint32_t r1, uint32_t r2, uint32_t r3) {
  asm volatile("stmatrix.sync.aligned.m8n8.x4.trans.shared.b16 [%0], {%1,%2,%3,%4};" ::"r"(addr), "r"(r0), "r"(r1), "r"(r2), "r"(r3) : "memory");
}
__device__ __forceinline__ float4 lds_f4(uint32_t addr) {
  float4 v; asm volatile("ld.shared.v4.f32 {%0,%1,%2,%3}, [%4];" : "=f"(v.x), "=f"(v.y), "=f"(v.z), "=f"(v.w) : "r"(addr) : "memory"); return v;
}
__device__ __forceinline__ float2 lds_f2(uint32_t addr) {
  float2 v; asm volatile("ld.shared.v2.f32 {%0,%1}, [%2];" : "=f"(v.x), "=f"(v.y) : "r"(addr) : "memory"); return v;
}
__device__ __forceinline__ void sts_f4(uint32_t addr, float a, float b, float c, float d) {
  asm volatile("st.shared.v4.f32 [%0], {%1,%2,%3,%4};" ::"r"(addr), "f"(a), "f"(b), "f"(c), "f"(d) : "memory");
}
__device__ __forceinline__ void sts_f2(uint32_t addr, float a, float b) {
  asm volatile("st.shared.v2.f32 [%0], {%1,%2};" ::"r"(addr), "f"(a), "f"(b) : "memory");
}
__device__ __forceinline__ void sts64(uint32_t addr, uint32_t a, uint32_t b) {
  asm volatile("st.shared.v2.b32 [%0], {%1,%2};" ::"r"(addr), "r"(a), "r"(b) : "memory");
}
__device__ __forceinline__ void lds64(uint32_t addr, uint32_t& a, uint32_t& b) {
  asm volatile("ld.shared.v2.b32 {%0,%1}, [%2];" : "=r"(a), "=r"(b) : "r"(addr) : "memory");
}
__device__ __forceinline__ uint32_t lds32(uint32_t addr) {
  uint32_t v; asm volatile("ld.shared.b32 %0, [%1];" : "=r"(v) : "r"(addr) : "memory"); return v;
}
__device__ __forceinline__ uint32_t lds16(uint32_t addr) {
  uint16_t v; asm volatile("ld.shared.u16 %0, [%1];" : "=h"(v) : "r"(addr) : "memory"); return v;
}
__device__ __forceinline__ void sts32(uint32_t addr, uint32_t v) { asm volatile("st.shared.b32 [%0], %1;" ::"r"(addr), "r"(v) : "memory"); }
__device__ __forceinline__ void sts16(uint32_t addr, uint32_t v) { asm volatile("st.shared.u16 [%0], %1;" ::"r"(addr), "h"((uint16_t)v) : "memory"); }
__device__ __forceinline__ uint32_t add_bf16x2(uint32_t a, uint32_t b) { uint32_t r; asm("add.rn.bf16x2 %0, %1, %2;" : "=r"(r) : "r"(a), "r"(b)); return r; }
__device__ __forceinline__ uint32_t mul_bf16x2(uint32_t a, uint32_t b) { uint32_t r; asm("mul.rn.bf16x2 %0, %1, %2;" : "=r"(r) : "r"(a), "r"(b)); return r; }
__device__ __forceinline__ void mma_tf32(float* c, float a0, float a1, float a2, float a3, float b0, float b1) {
  asm volatile("mma.sync.aligned.m16n8k8.row.col.f32.tf32.tf32.f32 {%0,%1,%2,%3}, {%4,%5,%6,%7}, {%8,%9}, {%0,%1,%2,%3};"
               : "+f"(c[0]), "+f"(c[1]), "+f"(c[2]), "+f"(c[3])
               : "r"(__float_as_uint(a0)), "r"(__float_as_uint(a1)), "r"(__float_as_uint(a2)), "r"(__float_as_uint(a3)),
                 "r"(__float_as_uint(b0)), "r"(__float_as_uint(b1)));
}
__device__ __forceinline__ float rcp_fast(float x) { float r; asm("rcp.approx.ftz.f32 %0, %1;" : "=f"(r) : "f"(x)); return r; }
struct cplx { float r, i; };
__device__ __forceinline__ cplx cmul(cplx a, cplx b) { return {fmaf(a.r, b.r, -(a.i * b.i)), fmaf(a.r, b.i, a.i * b.r)}; }
__device__ __forceinline__ cplx cmulc(cplx a, cplx b) { return {fmaf(a.r, b.r, -(a.i * b.i)), fmaf(-a.r, b.i, -(a.i * b.r))}; }
__device__ __forceinline__ cplx csq(cplx a) {
  float im;
  asm("{\n.reg .f32 u;\nmul.f32 u, %1, %2;\nmul.f32 %0, u, 0f40000000;\n}" : "=f"(im) : "f"(a.r), "f"(a.i));
  return {fmaf(a.r, a.r, -(a.i * a.i)), im};
}
__device__ __forceinline__ cplx cpolar(float x, float a) {
  float m, sn, cs;
  asm("ex2.approx.ftz.f32 %0, %1;" : "=f"(m) : "f"(x));
  asm("sin.approx.ftz.f32 %0, %1;" : "=f"(sn) : "f"(a));
  asm("cos.approx.ftz.f32 %0, %1;" : "=f"(cs) : "f"(a));
  return {m * cs, m * sn};
}
__device__ __forceinline__ cplx cexp_e(float zl, float zt, float e) {
  const float a = zt * e;
  return cpolar(zl * e, (a - rintf(a)) * 6.283185307179586f);
}

__device__ __forceinline__ void wgmma_rs_n128_tb(float* d, uint32_t a0, uint32_t a1, uint32_t a2, uint32_t a3, uint64_t db, int scale_d) {
  asm volatile("{\n.reg .pred p;\nsetp.ne.b32 p, %69, 0;\n"
    "wgmma.mma_async.sync.aligned.m64n128k16.f32.bf16.bf16 "
    "{%0, %1, %2, %3, %4, %5, %6, %7, %8, %9, %10, %11, %12, %13, %14, %15, "
    "%16, %17, %18, %19, %20, %21, %22, %23, %24, %25, %26, %27, %28, %29, %30, %31, "
    "%32, %33, %34, %35, %36, %37, %38, %39, %40, %41, %42, %43, %44, %45, %46, %47, "
    "%48, %49, %50, %51, %52, %53, %54, %55, %56, %57, %58, %59, %60, %61, %62, %63}, "
    "{%64, %65, %66, %67}, %68, p, 1, 1, 1;\n}\n"
    : "+f"(d[0]), "+f"(d[1]), "+f"(d[2]), "+f"(d[3]), "+f"(d[4]), "+f"(d[5]), "+f"(d[6]), "+f"(d[7]),
      "+f"(d[8]), "+f"(d[9]), "+f"(d[10]), "+f"(d[11]), "+f"(d[12]), "+f"(d[13]), "+f"(d[14]), "+f"(d[15]),
      "+f"(d[16]), "+f"(d[17]), "+f"(d[18]), "+f"(d[19]), "+f"(d[20]), "+f"(d[21]), "+f"(d[22]), "+f"(d[23]),
      "+f"(d[24]), "+f"(d[25]), "+f"(d[26]), "+f"(d[27]), "+f"(d[28]), "+f"(d[29]), "+f"(d[30]), "+f"(d[31]),
      "+f"(d[32]), "+f"(d[33]), "+f"(d[34]), "+f"(d[35]), "+f"(d[36]), "+f"(d[37]), "+f"(d[38]), "+f"(d[39]),
      "+f"(d[40]), "+f"(d[41]), "+f"(d[42]), "+f"(d[43]), "+f"(d[44]), "+f"(d[45]), "+f"(d[46]), "+f"(d[47]),
      "+f"(d[48]), "+f"(d[49]), "+f"(d[50]), "+f"(d[51]), "+f"(d[52]), "+f"(d[53]), "+f"(d[54]), "+f"(d[55]),
      "+f"(d[56]), "+f"(d[57]), "+f"(d[58]), "+f"(d[59]), "+f"(d[60]), "+f"(d[61]), "+f"(d[62]), "+f"(d[63])
    : "r"(a0), "r"(a1), "r"(a2), "r"(a3), "l"(db), "r"(scale_d));
}

__device__ __forceinline__ void wgmma_rs_n64_tb(float* d, uint32_t a0, uint32_t a1, uint32_t a2, uint32_t a3, uint64_t db, int scale_d) {
  asm volatile("{\n.reg .pred p;\nsetp.ne.b32 p, %37, 0;\n"
    "wgmma.mma_async.sync.aligned.m64n64k16.f32.bf16.bf16 "
    "{%0, %1, %2, %3, %4, %5, %6, %7, %8, %9, %10, %11, %12, %13, %14, %15, "
    "%16, %17, %18, %19, %20, %21, %22, %23, %24, %25, %26, %27, %28, %29, %30, %31}, "
    "{%32, %33, %34, %35}, %36, p, 1, 1, 1;\n}\n"
    : "+f"(d[0]), "+f"(d[1]), "+f"(d[2]), "+f"(d[3]), "+f"(d[4]), "+f"(d[5]), "+f"(d[6]), "+f"(d[7]),
      "+f"(d[8]), "+f"(d[9]), "+f"(d[10]), "+f"(d[11]), "+f"(d[12]), "+f"(d[13]), "+f"(d[14]), "+f"(d[15]),
      "+f"(d[16]), "+f"(d[17]), "+f"(d[18]), "+f"(d[19]), "+f"(d[20]), "+f"(d[21]), "+f"(d[22]), "+f"(d[23]),
      "+f"(d[24]), "+f"(d[25]), "+f"(d[26]), "+f"(d[27]), "+f"(d[28]), "+f"(d[29]), "+f"(d[30]), "+f"(d[31])
    : "r"(a0), "r"(a1), "r"(a2), "r"(a3), "l"(db), "r"(scale_d));
}

__device__ __forceinline__ void wgmma_rs_n32(float* d, uint32_t a0, uint32_t a1, uint32_t a2, uint32_t a3, uint64_t db, int scale_d) {
  asm volatile("{\n.reg .pred p;\nsetp.ne.b32 p, %21, 0;\n"
    "wgmma.mma_async.sync.aligned.m64n32k16.f32.bf16.bf16 "
    "{%0, %1, %2, %3, %4, %5, %6, %7, %8, %9, %10, %11, %12, %13, %14, %15}, "
    "{%16, %17, %18, %19}, %20, p, 1, 1, 0;\n}\n"
    : "+f"(d[0]), "+f"(d[1]), "+f"(d[2]), "+f"(d[3]), "+f"(d[4]), "+f"(d[5]), "+f"(d[6]), "+f"(d[7]),
      "+f"(d[8]), "+f"(d[9]), "+f"(d[10]), "+f"(d[11]), "+f"(d[12]), "+f"(d[13]), "+f"(d[14]), "+f"(d[15])
    : "r"(a0), "r"(a1), "r"(a2), "r"(a3), "l"(db), "r"(scale_d));
}

__device__ __forceinline__ void wgmma_rs_n64(float* d, uint32_t a0, uint32_t a1, uint32_t a2, uint32_t a3, uint64_t db, int scale_d) {
  asm volatile("{\n.reg .pred p;\nsetp.ne.b32 p, %37, 0;\n"
    "wgmma.mma_async.sync.aligned.m64n64k16.f32.bf16.bf16 "
    "{%0, %1, %2, %3, %4, %5, %6, %7, %8, %9, %10, %11, %12, %13, %14, %15, "
    "%16, %17, %18, %19, %20, %21, %22, %23, %24, %25, %26, %27, %28, %29, %30, %31}, "
    "{%32, %33, %34, %35}, %36, p, 1, 1, 0;\n}\n"
    : "+f"(d[0]), "+f"(d[1]), "+f"(d[2]), "+f"(d[3]), "+f"(d[4]), "+f"(d[5]), "+f"(d[6]), "+f"(d[7]),
      "+f"(d[8]), "+f"(d[9]), "+f"(d[10]), "+f"(d[11]), "+f"(d[12]), "+f"(d[13]), "+f"(d[14]), "+f"(d[15]),
      "+f"(d[16]), "+f"(d[17]), "+f"(d[18]), "+f"(d[19]), "+f"(d[20]), "+f"(d[21]), "+f"(d[22]), "+f"(d[23]),
      "+f"(d[24]), "+f"(d[25]), "+f"(d[26]), "+f"(d[27]), "+f"(d[28]), "+f"(d[29]), "+f"(d[30]), "+f"(d[31])
    : "r"(a0), "r"(a1), "r"(a2), "r"(a3), "l"(db), "r"(scale_d));
}

__device__ __forceinline__ void wgmma_rs_n24_tb(float* d, uint32_t a0, uint32_t a1, uint32_t a2, uint32_t a3, uint64_t db, int scale_d) {
  asm volatile("{\n.reg .pred p;\nsetp.ne.b32 p, %17, 0;\n"
    "wgmma.mma_async.sync.aligned.m64n24k16.f32.bf16.bf16 "
    "{%0, %1, %2, %3, %4, %5, %6, %7, %8, %9, %10, %11}, "
    "{%12, %13, %14, %15}, %16, p, 1, 1, 1;\n}\n"
    : "+f"(d[0]), "+f"(d[1]), "+f"(d[2]), "+f"(d[3]), "+f"(d[4]), "+f"(d[5]), "+f"(d[6]), "+f"(d[7]),
      "+f"(d[8]), "+f"(d[9]), "+f"(d[10]), "+f"(d[11])
    : "r"(a0), "r"(a1), "r"(a2), "r"(a3), "l"(db), "r"(scale_d));
}

__device__ __forceinline__ void wgmma_rs_n16_tb(float* d, uint32_t a0, uint32_t a1, uint32_t a2, uint32_t a3, uint64_t db, int scale_d) {
  asm volatile("{\n.reg .pred p;\nsetp.ne.b32 p, %13, 0;\n"
    "wgmma.mma_async.sync.aligned.m64n16k16.f32.bf16.bf16 "
    "{%0, %1, %2, %3, %4, %5, %6, %7}, "
    "{%8, %9, %10, %11}, %12, p, 1, 1, 1;\n}\n"
    : "+f"(d[0]), "+f"(d[1]), "+f"(d[2]), "+f"(d[3]), "+f"(d[4]), "+f"(d[5]), "+f"(d[6]), "+f"(d[7])
    : "r"(a0), "r"(a1), "r"(a2), "r"(a3), "l"(db), "r"(scale_d));
}

__device__ __forceinline__ void wgmma_rs_n24_f16_tb(float* d, uint32_t a0, uint32_t a1, uint32_t a2, uint32_t a3, uint64_t db, int scale_d) {
  asm volatile("{\n.reg .pred p;\nsetp.ne.b32 p, %17, 0;\n"
    "wgmma.mma_async.sync.aligned.m64n24k16.f32.f16.f16 "
    "{%0, %1, %2, %3, %4, %5, %6, %7, %8, %9, %10, %11}, "
    "{%12, %13, %14, %15}, %16, p, 1, 1, 1;\n}\n"
    : "+f"(d[0]), "+f"(d[1]), "+f"(d[2]), "+f"(d[3]), "+f"(d[4]), "+f"(d[5]), "+f"(d[6]), "+f"(d[7]),
      "+f"(d[8]), "+f"(d[9]), "+f"(d[10]), "+f"(d[11])
    : "r"(a0), "r"(a1), "r"(a2), "r"(a3), "l"(db), "r"(scale_d));
}

__device__ __forceinline__ uint32_t reglu2(const float* a) {
  uint32_t g, u, r;
  asm("cvt.rn.relu.bf16x2.f32 %0, %1, %2;" : "=r"(g) : "f"(a[1]), "f"(a[0]));
  asm("cvt.rn.bf16x2.f32 %0, %1, %2;" : "=r"(u) : "f"(a[33]), "f"(a[32]));
  asm("mul.rn.bf16x2 %0, %1, %2;" : "=r"(r) : "r"(g), "r"(u));
  return r;
}
__device__ __forceinline__ uint32_t fma_bf16x2(uint32_t a, uint32_t b, uint32_t c) {
  uint32_t r; asm("fma.rn.bf16x2 %0, %1, %2, %3;" : "=r"(r) : "r"(a), "r"(b), "r"(c)); return r;
}
__device__ __forceinline__ int step_chunk(int f, int s) { return s == 0 ? 8 : (f ^ (8 - s)); }

struct RawPair { uint32_t are, aim, bre, bim, cre, cim; uint16_t ldt, dsk; };
__device__ __forceinline__ float bfu(uint16_t v) { return __uint_as_float((uint32_t)v << 16); }
__device__ __forceinline__ uint32_t pack_f16(float lo, float hi) {
  uint32_t r; asm("cvt.rn.f16x2.f32 %0, %1, %2;" : "=r"(r) : "f"(hi), "f"(lo)); return r;
}
__device__ __forceinline__ uint32_t hmul2(uint32_t a, uint32_t b) { uint32_t r; asm("mul.rn.f16x2 %0, %1, %2;" : "=r"(r) : "r"(a), "r"(b)); return r; }
__device__ __forceinline__ uint32_t hfma2(uint32_t a, uint32_t b, uint32_t c) { uint32_t r; asm("fma.rn.f16x2 %0, %1, %2, %3;" : "=r"(r) : "r"(a), "r"(b), "r"(c)); return r; }
__device__ __forceinline__ uint32_t hfms2(uint32_t a, uint32_t b, uint32_t c) {
  uint32_t r; asm("{\n.reg .b32 n;\nneg.f16x2 n, %3;\nfma.rn.f16x2 %0, %1, %2, n;\n}" : "=r"(r) : "r"(a), "r"(b), "r"(c)); return r;
}
__device__ __forceinline__ void store_powers(uint32_t dst, cplx b0, cplx b1) {
  cplx p[2][8];
#pragma unroll
  for (int e = 0; e < 2; e++) {
    p[e][1] = e ? b1 : b0;
    p[e][2] = csq(p[e][1]); p[e][3] = cmul(p[e][2], p[e][1]); p[e][4] = csq(p[e][2]);
    p[e][5] = cmul(p[e][4], p[e][1]); p[e][6] = csq(p[e][3]); p[e][7] = cmul(p[e][6], p[e][1]);
  }
  sts128(dst, 0x3C003C00u, 0u, pack_f16(p[0][1].r, p[1][1].r), pack_f16(p[0][1].i, p[1][1].i));
#pragma unroll
  for (int j = 1; j < 4; j++)
    sts128(dst + j * 64, pack_f16(p[0][2 * j].r, p[1][2 * j].r), pack_f16(p[0][2 * j].i, p[1][2 * j].i),
           pack_f16(p[0][2 * j + 1].r, p[1][2 * j + 1].r), pack_f16(p[0][2 * j + 1].i, p[1][2 * j + 1].i));
}

__device__ __forceinline__ void kgen_channel(const RawPair& p, uint32_t blk, int wgi, int t) {
  const int lane = t & 31, ww = t >> 5, g = lane >> 2, tq = lane & 3;
  blk = __shfl_sync(0xffffffffu, blk, 0);
  const uint32_t tQ = blk + C_R2, tP = blk + C_R2 + 5120, tB = blk + C_Y0;
  {
    const float dt = rbf(expf(bfu(p.ldt)));
    float zl[2], zt[2];
#pragma unroll
    for (int e = 0; e < 2; e++) {
      zl[e] = fmaxf(dt * (e ? bf_hi(p.are) : bf_lo(p.are)) * 1.4426950408889634f, -1e30f);
      zt[e] = dt * (e ? bf_hi(p.aim) : bf_lo(p.aim)) * 0.15915494309189535f;
      zt[e] -= rintf(zt[e]);
    }
    const int s = (t & 63) >> 2;
    if (t < 64) {
      store_powers(tQ + s * 320 + tq * 16, cpolar(zl[0] * 4.f, zt[0] * 25.132741228718345f), cpolar(zl[1] * 4.f, zt[1] * 25.132741228718345f));
      store_powers(tP + s * 320 + tq * 16, cexp_e(zl[0], zt[0], 32.f), cexp_e(zl[1], zt[1], 32.f));
      sts128(blk + C_U + t * 16, 0, 0, 0, 0);
      if (t < 52) sts128(blk + (t < 7 ? C_PE + 16 * t : t < 27 ? C_PE + 1136 + 16 * (t - 7) : C_PO + 1136 + 16 * (t - 27)), 0, 0, 0, 0);
      if (t < 32) sts128(blk + C_T2 + 512 + 16 * t, 0, 0, 0, 0);
      if (t == 63) sts64(blk + C_MISC, p.dsk * 0x10001u, 0x3210u);
    } else {
      cplx c[2];
      c[0] = cmul({bf_lo(p.cre), bf_lo(p.cim)}, {dt * bf_lo(p.bre), dt * bf_lo(p.bim)});
      c[1] = cmul({bf_hi(p.cre), bf_hi(p.cim)}, {dt * bf_hi(p.bre), dt * bf_hi(p.bim)});
      const float mx = fmaxf(fmaxf(fabsf(c[0].r), fabsf(c[0].i)), fmaxf(fabsf(c[1].r), fabsf(c[1].i)));
      const uint32_t ex = max(__reduce_max_sync(0xffffffffu, __float_as_uint(mx)) >> 23, 16u);
      const float sc = __uint_as_float((262u - ex) << 23);
      if (lane == 0) sts32(blk + C_MISC + 4 * ww, (ex - 8u) << 23);
#pragma unroll
      for (int e = 0; e < 2; e++) {
        const cplx w1 = cpolar(zl[e], -zt[e] * 6.283185307179586f), w256 = cexp_e(zl[e], -zt[e], 256.f);
        const cplx w4 = csq(csq(w1));
        const cplx c0 = {c[e].r * sc, -c[e].i * sc};
        const cplx c1 = cmul(c0, w1), c2 = cmul(c1, w1), c3 = cmul(c2, w1), c4 = cmul(c0, w4);
        const cplx c256 = cmul(c0, w256), c258 = cmul(c2, w256), c260 = cmul(c4, w256);
        const cplx c512 = cmul(c256, w256), c516 = cmul(c260, w256), c768 = cmul(c512, w256), c772 = cmul(c516, w256);
        const cplx c1032 = cmul(cmul(c772, w4), w256), c1288 = cmul(c1032, w256), c1544 = cmul(c1288, w256), c1800 = cmul(c1544, w256);
        const uint32_t d = tB + s * 256 + (2 * tq + e) * 16;
        sts128(d, pack_f16(c2.r, c1.r), pack_f16(c4.r, c3.r), pack_f16(c258.r, c256.r), pack_f16(c260.r, c260.r));
        sts128(d + 128, pack_f16(c2.i, c1.i), pack_f16(c4.i, c3.i), pack_f16(c258.i, c256.i), pack_f16(c260.i, c260.i));
        sts128(d + 4096, pack_f16(c1.r, c0.r), pack_f16(c3.r, c2.r), pack_f16(c256.r, c256.r), pack_f16(c260.r, c258.r));
        sts128(d + 4224, pack_f16(c1.i, c0.i), pack_f16(c3.i, c2.i), pack_f16(c256.i, c256.i), pack_f16(c260.i, c258.i));
        sts128(d + 8192, pack_f16(c516.r, c512.r), pack_f16(c772.r, c768.r), pack_f16(c1032.r, c1288.r), pack_f16(c1544.r, c1800.r));
        sts128(d + 8320, pack_f16(c516.i, c512.i), pack_f16(c772.i, c768.i), pack_f16(c1032.i, c1288.i), pack_f16(c1544.i, c1800.i));
      }
    }
    SUB(1);
    fence_async_smem();
  }
  SUB(2);
  wg_bar(wgi);
  SUB(3);
  float acc[2][12];
  {
    const uint32_t rq = tQ + (g >> 1) * 64 + tq * 16 + (g & 1) * 8, rp = tP + ww * 64 + tq * 16;
    const uint64_t db = mkdesc(tB, 128, 4096, 0);
#pragma unroll
    for (int h = 0; h < 2; h++) {
      uint32_t A[8][4];
#pragma unroll
      for (int k = 0; k < 8; k++) {
        uint32_t qr, qi, lr, li, hr, hi;
        lds64(rq + (8 * h + k) * 320, qr, qi);
        lds128(rp + (8 * h + k) * 320, lr, li, hr, hi);
        A[k][0] = hfms2(lr, qr, hmul2(li, qi)); A[k][2] = hfma2(lr, qi, hmul2(li, qr));
        A[k][1] = hfms2(hr, qr, hmul2(hi, qi)); A[k][3] = hfma2(hr, qi, hmul2(hi, qr));
      }
      wg_fence();
#pragma unroll
      for (int k = 0; k < 8; k++) wgmma_rs_n24_f16_tb(acc[h], A[k][0], A[k][1], A[k][2], A[k][3], db + (8 * h + k) * 16, k != 0);
      wg_commit();
    }
  }
  SUB(4);
  const float2 us = lds_f2(blk + C_MISC + 8);
  wg_wait<0>();
  SUB(5);
  reg_fence<12>(acc[0]); reg_fence<12>(acc[1]);
  float v[12];
#pragma unroll
  for (int i = 0; i < 12; i++) v[i] = fmaf(acc[0][i], us.x, acc[1][i] * us.y);
  const int r = 16 * ww + g;
  const float t512 = __shfl_down_sync(0xffffffffu, v[2], 1);
  if (t == 126) v[2] -= t512;
  if (t == 127) { v[7] -= v[6]; v[2] = v[3] = v[6] = 0.f; }
  const uint32_t o = blk + 4 * (28 + 2 * r + (tq & 1) + 128 * (tq >> 1));
  sts32(o + C_PE + 4, pack_bf16(v[0], v[1]));
  sts32(o + C_PE + 68, pack_bf16(v[2], v[3]));
  sts32(o + C_PO, pack_bf16(v[4], v[5]));
  sts32(o + C_PO + 64, pack_bf16(v[6], v[7]));
  if (t == 0) sts32(blk + C_PE + 112, pack_bf16(v[5], 0.f));
  if (t == 125) sts32(blk + C_T2 + 512, pack_bf16(v[10], v[10]));
  if ((g & 1) == 0) {
    const uint32_t wl = pack_bf16(v[8], v[9]), wh = pack_bf16(v[10], v[11]);
    if (tq < 2) {
      const uint32_t f = blk + C_T2 + 4 * (64 + 32 * tq + (r >> 1));
      sts32(f, wl); sts32(f + 16, wh);
    } else {
      const uint32_t f = blk + C_T3 + 256 + 2 * ((64 * (tq - 2) + (r >> 1)) ^ 1);
      sts16(f, wl); sts16(f + 64, wl >> 16); sts16(f + 8, wh); sts16(f + 72, wh >> 16);
    }
  }
  SUB(6);
}

__device__ __forceinline__ uint32_t chunk_off(int a) { return (uint32_t)(a * 16) ^ (uint32_t)((a << 1) & 0x30); }
__device__ __forceinline__ uint32_t u_chunk(uint32_t blk, int a) { return blk + C_U + chunk_off(a + 64); }

__device__ __forceinline__ void window_chunk(uint32_t blk, int a) {
  uint32_t p[4], o[4], n0, n1;
  lds128(u_chunk(blk, a - 1), p[0], p[1], p[2], p[3]);
  lds128(u_chunk(blk, a), o[0], o[1], o[2], o[3]);
  lds64(u_chunk(blk, a + 1), n0, n1);
  float P[18];
  P[0] = 0.f;
  P[1] = bf_hi(p[1]);
  P[2] = P[1] + bf_lo(p[2]); P[3] = P[2] + bf_hi(p[2]); P[4] = P[3] + bf_lo(p[3]); P[5] = P[4] + bf_hi(p[3]);
#pragma unroll
  for (int i = 0; i < 4; i++) { P[6 + 2 * i] = P[5 + 2 * i] + bf_lo(o[i]); P[7 + 2 * i] = P[6 + 2 * i] + bf_hi(o[i]); }
  P[14] = P[13] + bf_lo(n0); P[15] = P[14] + bf_hi(n0);
  sts128(blk + C_R2 + (a + 8) * 32, pack_bf16(P[3] - P[0], P[4] - P[1]), pack_bf16(P[5] - P[2], P[6] - P[3]),
         pack_bf16(P[7] - P[4], P[8] - P[5]), pack_bf16(P[9] - P[6], P[10] - P[7]));
  sts128(blk + C_R2 + (a + 8) * 32 + 16, pack_bf16(P[8] - P[3], P[9] - P[4]), pack_bf16(P[10] - P[5], P[11] - P[6]),
         pack_bf16(P[12] - P[7], P[13] - P[8]), pack_bf16(P[14] - P[9], P[15] - P[10]));
  if (a >= -2 && a < 127) {
    P[16] = P[15] + bf_lo(n1); P[17] = P[16] + bf_hi(n1);
    const uint32_t g0 = blk + C_G0 + (a + 2) * 16, g1 = blk + C_G1 + (a + 1) * 16;
    sts128((a & 1) ? g1 : g0, pack_bf16(P[10] - P[1], P[11] - P[2]), pack_bf16(P[12] - P[3], P[13] - P[4]),
           pack_bf16(P[14] - P[5], P[15] - P[6]), pack_bf16(P[16] - P[7], P[17] - P[8]));
    sts128((a & 1) ? g0 : g1, pack_bf16(P[9] - P[2], P[10] - P[3]), pack_bf16(P[11] - P[4], P[12] - P[5]),
           pack_bf16(P[13] - P[6], P[14] - P[7]), pack_bf16(P[15] - P[8], P[16] - P[9]));
  }
}

template <bool HI>
__device__ __forceinline__ void conv_final(uint32_t blk, int n, int ch, uint32_t dsk2) {
  uint32_t y[4], f[4], uv[4], xv[4];
  const uint32_t co = blk + chunk_off(n);
  lds128(co + C_Y0, y[0], y[1], y[2], y[3]);
  lds128((HI || n >= 36) ? blk + C_Y1 + chunk_off(n - 36) : blk + C_U, f[0], f[1], f[2], f[3]);
  lds128(co + C_U + 1024, uv[0], uv[1], uv[2], uv[3]);
  lds128(co + C_X, xv[0], xv[1], xv[2], xv[3]);
  if (HI || n >= 64) {
    uint32_t e[4];
    lds128(blk + C_YF + (n - 64) * 16, e[0], e[1], e[2], e[3]);
    if (HI) {
      const uint32_t kb = lds32(blk + C_T2 + 512) ^ 0x80008000u;
      uint32_t z[4], p[4], q0, q1;
      lds128(blk + C_Y3 + (n - 128) * 16, z[0], z[1], z[2], z[3]);
      lds128(u_chunk(blk, n - 129), p[0], p[1], p[2], p[3]);
      lds64(co + C_U - 1024, q0, q1);
      z[0] = fma_bf16x2(kb, __byte_perm(p[1], p[2], 0x5432), z[0]); z[1] = fma_bf16x2(kb, __byte_perm(p[2], p[3], 0x5432), z[1]);
      z[2] = fma_bf16x2(kb, __byte_perm(p[3], q0, 0x5432), z[2]); z[3] = fma_bf16x2(kb, __byte_perm(q0, q1, 0x5432), z[3]);
#pragma unroll
      for (int k = 0; k < 4; k++) e[k] = add_bf16x2(e[k], z[k]);
    }
#pragma unroll
    for (int k = 0; k < 4; k++) f[k] = add_bf16x2(f[k], e[k]);
  } else if (n == 63) {
    const float kv = bf_hi(lds32(blk + C_T2 + 256));
    const uint32_t w = lds32(u_chunk(blk, 0));
    f[3] = pack_bf16(fmaf(kv, bf_lo(w), bf_lo(f[3])), fmaf(kv, bf_lo(w) + bf_hi(w), bf_hi(f[3])));
  }
  uint32_t h[4];
#pragma unroll
  for (int k = 0; k < 4; k++) h[k] = add_bf16x2(xv[k], add_bf16x2(add_bf16x2(y[k], f[k]), mul_bf16x2(uv[k], dsk2)));
  ((uint4*)(g_hT + ch * L_SEQ))[n] = make_uint4(h[0], h[1], h[2], h[3]);
}

__device__ __forceinline__ uint32_t opaque_copy(uint32_t v, uint32_t ident) {
  uint32_t r; asm volatile("prmt.b32 %0, %1, 0, %2;" : "=r"(r) : "r"(v), "r"(ident)); return r;
}
__device__ __forceinline__ void conv_channel(uint32_t blk, int wgi, int t, int ch) {
  const int lane = t & 31, ww = t >> 5;
  blk = __shfl_sync(0xffffffffu, blk, 0);
  uint32_t dsk2, ident;
  lds64(blk + C_MISC, dsk2, ident);
  float nr[32];
  {
    const uint32_t an = blk + ((lane & 4) ? C_PO : C_PE) + 4 * (20 + 144 * (ww >> 1) + 8 * (ww & 1) + (lane >> 3) - (lane & 3));
    uint32_t A[18][4];
    A[0][2] = lds32(an - 16);
#pragma unroll
    for (int n = 0; n < 18; n++) { A[n][0] = lds32(an + n * 32); A[n][1] = lds32(an + n * 32 + 16); }
#pragma unroll
    for (int n = 0; n < 18; n++) {
      if (n) A[n][2] = opaque_copy(A[n - 1][1], ident);
      A[n][3] = opaque_copy(A[n][0], ident);
    }
    const uint64_t dn = mkdesc(blk + C_U + 1024, 16, 512, 2);
    SUB(1);
    wg_fence();
#pragma unroll
    for (int n = 0; n < 18; n++) wgmma_rs_n64(nr, A[n][0], A[n][1], A[n][2], A[n][3], dn + (2 * (1 - (n & 1)) - 4 * (n >> 1)), n != 0);
    wg_commit();
    SUB(2);
#pragma unroll 1
    for (int a = t - 1; a < 199; a += 128) window_chunk(blk, a < 192 ? a : a - 200);
    fence_async_smem();
    wg_wait<0>();
    reg_fence<32>(nr);
  }
  SUB(3);
  float f24[12], f16[8], f3[8];
  {
    const uint32_t at = blk + 4 * (16 * ww + (lane >> 2) - (lane & 3));
    uint32_t A[24][4];
#pragma unroll
    for (int n = 0; n < 24; n++) {
      const uint32_t aa = at + (n < 16 ? C_T2 + 4 * (128 - 8 * n) : C_T3 + 4 * (64 - 8 * (n - 16)));
      A[n][0] = lds32(aa); A[n][2] = lds32(aa - 16);
      if (n == 0 || n == 16) { A[n][1] = lds32(aa + 32); A[n][3] = lds32(aa + 16); }
    }
    {
      const uint32_t st = blk + ((ww >> 1) ? C_Y1 : C_Y0) + chunk_off(4 * ((lane >> 4) * 8 + (lane & 7)) + 2 * (ww & 1) + ((lane >> 3) & 1));
#pragma unroll
      for (int q = 0; q < 4; q++)
        stsm4_t(st + q * 1024, pack_bf16(nr[8 * q], nr[8 * q + 1]), pack_bf16(nr[8 * q + 2], nr[8 * q + 3]),
                pack_bf16(nr[8 * q + 4], nr[8 * q + 5]), pack_bf16(nr[8 * q + 6], nr[8 * q + 7]));
    }
#pragma unroll
    for (int n = 0; n < 24; n++)
      if (n != 0 && n != 16) { A[n][1] = opaque_copy(A[n - 1][0], ident); A[n][3] = opaque_copy(A[n - 1][2], ident); }
    const uint64_t d2 = mkdesc(blk + C_R2, 128, 2048, 0), d3 = mkdesc(blk + C_G0, 128, C_G1 - C_G0, 0);
    wg_bar(wgi);
    SUB(4);
    wg_fence();
#pragma unroll
    for (int n = 0; n < 24; n++) {
      if (n < 7) wgmma_rs_n16_tb(f16, A[n][0], A[n][1], A[n][2], A[n][3], d2 + (16 * n + 16), n != 0);
      else if (n < 16) wgmma_rs_n24_tb(f24, A[n][0], A[n][1], A[n][2], A[n][3], d2 + (16 * n - 112), n != 7);
      else wgmma_rs_n16_tb(f3, A[n][0], A[n][1], A[n][2], A[n][3], d3 + 16 * (n - 16), n != 16);
    }
    wg_commit();
    wg_wait<0>();
    reg_fence<12>(f24); reg_fence<8>(f16); reg_fence<8>(f3);
  }
  SUB(5);
  {
    const uint32_t sf = blk + C_YF + (16 * ww + (lane & 15)) * 16 + (lane >> 4) * 1024;
    stsm4(sf + 1024, pack_bf16(f24[4] + f16[0], f24[5] + f16[1]), pack_bf16(f24[6] + f16[2], f24[7] + f16[3]),
          pack_bf16(f24[8] + f16[4], f24[9] + f16[5]), pack_bf16(f24[10] + f16[6], f24[11] + f16[7]));
    asm volatile("stmatrix.sync.aligned.m8n8.x2.shared.b16 [%0], {%1,%2};" ::"r"(sf), "r"(pack_bf16(f24[0], f24[1])),
                 "r"(pack_bf16(f24[2], f24[3])) : "memory");
    stsm4(blk + C_Y3 + (16 * ww + (lane & 15)) * 32 + (lane >> 4) * 16, pack_bf16(f3[0], f3[1]), pack_bf16(f3[2], f3[3]),
          pack_bf16(f3[4], f3[5]), pack_bf16(f3[6], f3[7]));
  }
  wg_bar(wgi);
  SUB(6);
  conv_final<false>(blk, t, ch, dsk2);
  conv_final<true>(blk, t + 128, ch, dsk2);
}

struct SsmPtrs { const uint16_t *x, *are, *aim, *bre, *bim, *cre, *cim, *ldt, *dsk; const uint8_t *wg, *wu, *wd; };
__device__ __forceinline__ RawPair load_pair(const SsmPtrs& P, int ch, int t) {
  const int i = ch * (N_STATE / 2) + (t & 63);
  typedef const uint32_t* wp;
  return {__ldg((wp)P.are + i), __ldg((wp)P.aim + i), __ldg((wp)P.bre + i), __ldg((wp)P.bim + i), __ldg((wp)P.cre + i),
          __ldg((wp)P.cim + i), __ldg(P.ldt + ch), __ldg(P.dsk + ch)};
}

struct Ring { int st; uint32_t ph; };
__device__ __forceinline__ void ring_next(Ring& r) { if (++r.st == NSTAGE) { r.st = 0; r.ph ^= 1; } }

template <bool HAS_PREV>
__device__ __forceinline__ void down_step(float* cur, float* prev, const uint32_t* H, Ring& rg, int& prev_st, uint32_t sb,
                                          uint32_t stage_addr, uint32_t stfull_bar, int lane) {
  reg_fence<32>(cur);
#pragma unroll
  for (int s = 0; s < NST2; s++) {
    const uint64_t db = mkdesc(sb + SM_RING + rg.st * STAGE_BYTES, 0, 1024, 1);
    const int cur_st = rg.st;
#pragma unroll
    for (int k = 0; k < KS2; k++) {
      const int kk = 4 * (s * KS2 + k);
      if (k == KS2 - G2) {
        ring_next(rg);
        mbar_wait(sb + SM_BAR + 8 * (B_FULL + rg.st), rg.ph);
      }
      if ((k % G2) == 0 && (HAS_PREV || s > 0 || k == 0 || k >= 4)) wg_fence();
      wgmma_rs_n64_tb(cur, H[kk], H[kk + 1], H[kk + 2], H[kk + 3], db + k * 128, (s | k) != 0);
      if ((k % G2) == G2 - 1 && (HAS_PREV || s > 0 || k >= 3)) wg_commit();
      if (k == G2 - 1 && (HAS_PREV || s > 0)) {
        wg_wait<1>();
        if (lane == 0) mbar_arrive(sb + SM_BAR + 8 * (B_EMPTY + prev_st));
      }
    }
    prev_st = cur_st;
    if (HAS_PREV && s == 0) {
      reg_fence<32>(prev);
#pragma unroll
      for (int q = 0; q < 4; q++)
        sts128(stage_addr + q * 512, pack_bf16(prev[8 * q], prev[8 * q + 1]), pack_bf16(prev[8 * q + 2], prev[8 * q + 3]),
               pack_bf16(prev[8 * q + 4], prev[8 * q + 5]), pack_bf16(prev[8 * q + 6], prev[8 * q + 7]));
      fence_async_smem();
      __syncwarp();
      if (lane == 0) mbar_arrive(stfull_bar);
    }
  }
}

__global__ void __launch_bounds__(NTHREADS, 1)
fused_kernel(const __grid_constant__ CUtensorMap tmWg, const __grid_constant__ CUtensorMap tmWu,
             const __grid_constant__ CUtensorMap tmWd, const __grid_constant__ CUtensorMap tmHT,
             const SsmPtrs P, __nv_bfloat16* __restrict__ out) {
  extern __shared__ __align__(1024) uint8_t smem[];
  const uint32_t sb = smem_u32(smem);
  const int tid = threadIdx.x, warp = tid >> 5, lane = tid & 31;
  const int mt = blockIdx.x >> 3, fs = blockIdx.x & 7;
  float* s_r2 = (float*)(smem + SM_BAR + 512);
  TS_INIT();
  TS(0, tid == 0);
  volatile unsigned* s_epoch = (volatile unsigned*)(smem + SM_BAR + 8 * B_COUNT);
  {
    const int wgi = __shfl_sync(0xffffffffu, tid >> 7, 0), t = tid & 127;
    const int ch0 = (blockIdx.x >> 1) * 9 + (blockIdx.x & 1) * 5, nch = 5 - (blockIdx.x & 1);
    const bool two = wgi + 3 < nch;
    const bool do_ln = wgi == 2;
    const int rb = blockIdx.x;
    const uint32_t ln = sb + SM_LN;
    if (do_ln) {
#pragma unroll
      for (int i = 0; i < 9; i++) {
        const int c = t + 128 * i, r = c / 72;
        asm volatile("cp.async.cg.shared.global [%0], [%1], 16;" ::"r"(ln + c * 16 + r * 16 + (r >> 3) * 64),
                     "l"(P.x + rb * 16 * D_MODEL + c * 8) : "memory");
      }
    }
    RawPair m0 = load_pair(P, ch0 + wgi, t);
    const RawPair m1 = load_pair(P, ch0 + (two ? wgi + 3 : wgi), t);
    if (tid == 288) {
      const unsigned ep = *(volatile unsigned*)&g_epoch + 1;
      if (sb & 1023) __trap();
#pragma unroll
      for (int i = 0; i < B_COUNT; i++)
        mbar_init(sb + SM_BAR + 8 * i, ((i >= B_EMPTY && i < B_HFULL) || i == B_HFREE) ? 8 : (i >= B_STFULL && i < B_C8) ? 4 : 1);
      asm volatile("fence.mbarrier_init.release.cluster;" ::: "memory");
      *s_epoch = ep;
    }
    if (warp == 10 && lane < 4)
      asm volatile("prefetch.tensormap [%0];" ::"l"(lane == 0 ? &tmWg : lane == 1 ? &tmWu : lane == 2 ? &tmWd : &tmHT) : "memory");
    if (do_ln) {
      const int g = lane >> 2, ww = warp & 3;
      asm volatile("cp.async.wait_all;" ::: "memory");
      wg_bar(wgi);
      TS(50, tid == 256);
      {
        const int c0 = 4 * (ww >> 1) + (ww & 1);
        const uint32_t la = ln + (8 * ((lane >> 1) & 1) + 2 * (lane >> 3) + (lane & 1)) * LN_PITCH + ((lane >> 1) & 1) * 64 +
                            (c0 + 2 * ((lane >> 2) & 1)) * 16;
        uint4* gp = g_xT + (8 * (c0 + (lane & 2)) + g) * 256 + (chunk_off(rb * 2 + (lane & 1)) >> 4);
#pragma unroll
        for (int i = 0; i < 9; i++) {
          uint4 v;
          ldsm4_t(la + i * 128, v.x, v.y, v.z, v.w);
          gp[i * 64 * 256] = v;
        }
      }
      {
        float sA[4] = {0, 0, 0, 0}, qa[4] = {0, 0, 0, 0}, qb[4] = {0, 0, 0, 0};
        const uint32_t la = ln + (lane & 15) * LN_PITCH + ((lane >> 3) & 1) * 64 + (lane >> 4) * 16 + ww * 288;
#pragma unroll
        for (int k = 0; k < 9; k++) {
          uint32_t x0, x1, x2, x3;
          ldsm4(la + k * 32, x0, x1, x2, x3);
          mma_bf16(sA, x0, x1, x2, x3, 0x3F803F80u, 0x3F803F80u);
          mma_bf16(qa, x0, x1, x2, x3, x0, x2);
          mma_bf16(qb, x0, x1, x2, x3, x1, x3);
        }
        if ((lane & 3) == (g >> 1)) {
          sts_f2(ln + LN_STAT + g * 32 + ww * 8, sA[0], (g & 1) ? qa[1] : qa[0]);
          sts_f2(ln + LN_STAT + (g + 8) * 32 + ww * 8, sA[2], (g & 1) ? qb[3] : qb[2]);
        }
      }
      TS(51, tid == 256);
      if (warp == 8) {
        named_bar(4, 128);
        if (lane < 16) {
          const float4 p0 = lds_f4(ln + LN_STAT + lane * 32), p1 = lds_f4(ln + LN_STAT + lane * 32 + 16);
          const float mean = ((p0.x + p0.z) + (p1.x + p1.z)) * (1.0f / D_MODEL);
          const float var = fmaxf(((p0.y + p0.w) + (p1.y + p1.w)) * (1.0f / D_MODEL) - mean * mean, 0.f);
          float sd;
          asm("sqrt.approx.f32 %0, %1;" : "=f"(sd) : "f"(rbf(rbf(var) + 1e-5f)));
          uint8_t* sp = (uint8_t*)g_stat + (rb * 2 + (lane >> 3)) * 48;
          ((float*)sp)[lane & 7] = rcp_fast(rbf(sd));
          ((uint16_t*)(sp + 32))[lane & 7] = (uint16_t)pack_bf16(mean, 0.f);
        }
        __syncwarp();
        TS(11, lane == 0);
        if (lane == 0) {
          asm volatile("red.release.gpu.global.add.u32 [%0], 1;" ::"l"(&g_done[32]) : "memory");
          TS(40, true);
          wait_flag(&g_done[32], *s_epoch * NCTA);
          mbar_expect_tx(sb + SM_BAR + 8 * B_XS, 4096 * nch + 12288);
        }
        __syncwarp();
        TS(42, lane == 0);
        if (lane <= nch) {
          fence_async_global();
          if (lane < nch) bulk_load(sb + lane * CHS + C_X, g_xT + (ch0 + lane) * 256, 4096, sb + SM_BAR + 8 * B_XS);
          else bulk_load(sb + SM_STAT, g_stat, 12288, sb + SM_BAR + 8 * B_XS);
        }
        __syncwarp();
      } else {
        asm volatile("bar.arrive 4, 128;" ::: "memory");
      }
      if (warp == 9) asm volatile("bar.arrive 6, 288;" ::: "memory");
    }
#pragma unroll 1
    for (int i = 0; i <= (int)two; i++) {
      kgen_channel(m0, sb + (wgi + 3 * i) * CHS, wgi, t);
      TS(12, tid == 0 && i == 0);
      m0 = m1;
    }
    TS(13, tid == 0);
    TS(41, tid == 256);
    if (wgi < 2) {
      named_bar(6, 288);
      mbar_wait(sb + SM_BAR + 8 * B_XS, 0);
      TS(43, tid == 0);
      const float4 r0 = lds_f4(sb + SM_STAT + tid * 48), r1 = lds_f4(sb + SM_STAT + tid * 48 + 16);
      uint32_t mm[4];
      lds128(sb + SM_STAT + tid * 48 + 32, mm[0], mm[1], mm[2], mm[3]);
      const uint32_t co = sb + chunk_off(tid);
#pragma unroll
      for (int c = 0; c < 5; c++) {
        if (c < nch) {
          uint32_t x[4];
          lds128(co + c * CHS + C_X, x[0], x[1], x[2], x[3]);
#pragma unroll
          for (int q = 0; q < 4; q++) x[q] = sub_bf16x2(x[q], mm[q]);
          sts128(co + c * CHS + C_U + 1024, pack_bf16(bf_lo(x[0]) * r0.x, bf_hi(x[0]) * r0.y), pack_bf16(bf_lo(x[1]) * r0.z, bf_hi(x[1]) * r0.w),
                 pack_bf16(bf_lo(x[2]) * r1.x, bf_hi(x[2]) * r1.y), pack_bf16(bf_lo(x[3]) * r1.z, bf_hi(x[3]) * r1.w));
        }
      }
      fence_async_smem();
      asm volatile("bar.arrive 7, 384;" ::: "memory");
      named_bar(5, 256);
    } else {
      named_bar(7, 384);
    }
    TS(45, tid == 0);
    TS(47, tid == 256);
#pragma unroll 1
    for (int c = wgi; c < nch; c += 3) {
      conv_channel(sb + c * CHS, wgi, t, ch0 + c);
      TS(46, tid == 256);
      TS(52 + c / 3, tid == 0);
      TS(54 + c / 3, tid == 128);
    }
    TS(17, tid == 0);
    fence_async_smem();
    __syncthreads();
    TS(18, tid == 0);
    if (tid == 288) asm volatile("red.release.gpu.global.add.u32 [%0], 1;" ::"l"(&g_done[0]) : "memory");
  }
  const unsigned epoch = *s_epoch;

  if (warp >= 8) {
    asm volatile("setmaxnreg.dec.sync.aligned.u32 24;");
    if (warp == 8) {
      if (lane == 0) {
        Ring rg{0, 1};
        int n = 0;
#pragma unroll 1
        for (int c = 0; c < 9; c++)
#pragma unroll 1
          for (int s = 0; s < NST1; s++, n++) {
            if (n == HBOX8_STAGE) {
              wait_flag(&g_done[0], epoch * NCTA);
              TS(44, true);
              fence_async_global();
              TS(21, lane == 0);
              if (blockIdx.x == 0) *(volatile unsigned*)&g_epoch = epoch;
#pragma unroll 1
              for (int w = 0; w < 2; w++)
#pragma unroll 1
                for (int j = 0; j < 9; j++) {
                  const uint32_t bar = sb + SM_BAR + 8 * (B_HFULL + w * 9 + j);
                  const uint32_t dst = j < 8 ? sb + SM_PARK + w * 65536 + j * 8192 : sb + HBOX8_OFF + w * 8192;
                  mbar_expect_tx(bar, 8192);
                  tma_load_2d(dst, &tmHT, mt * 128 + w * 64, j * 64, bar);
                }
              mbar_wait(sb + SM_BAR + 8 * B_HFREE, 0);
            }
            {
              mbar_wait(sb + SM_BAR + 8 * (B_EMPTY + rg.st), rg.ph);
              const uint32_t bar = sb + SM_BAR + 8 * (B_FULL + rg.st), dst = sb + SM_RING + rg.st * STAGE_BYTES;
              mbar_expect_tx(bar, STAGE_BYTES);
              tma_load_2d(dst, &tmWg, fs * 576 + (c == 8 ? 0 : c + 1) * 64, s * KS1 * 16, bar);
              tma_load_2d(dst + STAGE_BYTES / 2, &tmWu, fs * 576 + (c == 8 ? 0 : c + 1) * 64, s * KS1 * 16, bar);
            }
            ring_next(rg);
          }
#pragma unroll 1
        for (int c = 0; c < 9; c++) {
          const int ch = step_chunk(fs, c);
#pragma unroll 1
          for (int s = 0; s < NST2; s++) {
            mbar_wait(sb + SM_BAR + 8 * (B_EMPTY + rg.st), rg.ph);
            const uint32_t bar = sb + SM_BAR + 8 * (B_FULL + rg.st), dst = sb + SM_RING + rg.st * STAGE_BYTES;
            mbar_expect_tx(bar, STAGE_BYTES);
            tma_load_2d(dst, &tmWd, ch * 64, fs * 576 + s * KS2 * 16, bar);
            ring_next(rg);
          }
        }
#pragma unroll 1
        for (int w = 0; w < 2; w++) {
          mbar_wait(sb + SM_BAR + 8 * (B_EMPTY + rg.st), rg.ph);
          const uint32_t bar = sb + SM_BAR + 8 * (B_FULL + rg.st), dst = sb + SM_RING + rg.st * STAGE_BYTES;
          mbar_expect_tx(bar, 8192);
          tma_load_2d(dst, &tmHT, mt * 128 + w * 64, fs * 64, bar);
          ring_next(rg);
        }
      }
    } else if (warp <= 10) {
      if (lane == 0) {
        const int w = warp - 9;
#pragma unroll 1
        for (int s = 0; s < 8; s++) {
          const int slot = ((mt * 9 + step_chunk(fs, s)) * 8 + fs) * 2 + w;
          mbar_wait(sb + SM_BAR + 8 * (B_STFULL + w * 8 + s), 0);
          bulk_store(g_part + (size_t)slot * 512, sb + SM_PARK + w * 65536 + s * 8192, 8192);
          bulk_commit();
          bulk_wait0();
          st_release(&g_flag[slot], epoch);
          TS(13 + s, w == 0 && s >= 6);
        }
      }
    } else {
      const int base = (mt * 9 + 8) * 16;
      mbar_wait(sb + SM_BAR + 8 * (B_STFULL + 1), 0);
      mbar_wait(sb + SM_BAR + 8 * (B_STFULL + 9), 0);
      if (lane < 9) wait_flag(&g_flag[base + (lane < 8 ? lane * 2 + (fs >> 2) : fs * 2 + 1 - (fs >> 2))], epoch);
      __syncwarp();
      const uint32_t bar = sb + SM_BAR + 8 * B_C8;
      if (lane == 0) mbar_expect_tx(bar, 16384);
      __syncwarp();
      if (lane < 8) {
        fence_async_global();
        bulk_load(sb + SM_PARK + (lane >> 2) * 65536 + (lane & 3) * 2048,
                  g_part + (size_t)(base + lane * 2 + (fs >> 2)) * 512 + (fs & 3) * 128, 2048, bar);
      }
      const int row = mt * 128 + fs * 16 + (lane >> 2);
      mbar_wait(bar, 0);
#pragma unroll 1
      for (int q = 0; q < 4; q++) {
        float a[8] = {0, 0, 0, 0, 0, 0, 0, 0};
        const int col = 512 + q * 16 + 2 * (lane & 3);
#pragma unroll 1
        for (int src = 0; src < 8; src++) {
          uint32_t v0, v1, v2, v3;
          lds128(sb + SM_PARK + (src >> 2) * 65536 + (src & 3) * 2048 + q * 512 + lane * 16, v0, v1, v2, v3);
          a[0] += bf_lo(v0); a[1] += bf_hi(v0); a[2] += bf_lo(v1); a[3] += bf_hi(v1);
          a[4] += bf_lo(v2); a[5] += bf_hi(v2); a[6] += bf_lo(v3); a[7] += bf_hi(v3);
        }
        const __nv_bfloat16* hp = g_hT + col * L_SEQ + row;
        const float r2a = s_r2[fs * 16 + (lane >> 2)], r2b = s_r2[fs * 16 + (lane >> 2) + 8];
#pragma unroll
        for (int e = 0; e < 8; e++)
          a[e] = fmaf(a[e], (e & 2) ? r2b : r2a, bfu(__ldcg((const uint16_t*)hp + ((e & 1) + ((e >> 2) << 3)) * L_SEQ + ((e >> 1) & 1) * 8)));
        uint32_t* o = (uint32_t*)(out + (size_t)row * D_MODEL + col);
        o[0] = pack_bf16(a[0], a[1]);
        o[8 * D_MODEL / 2] = pack_bf16(a[2], a[3]);
        o[4] = pack_bf16(a[4], a[5]);
        o[8 * D_MODEL / 2 + 4] = pack_bf16(a[6], a[7]);
      }
    }
  } else {
    asm volatile("setmaxnreg.inc.sync.aligned.u32 240;");
    const int w = warp >> 2, ww = warp & 3, g = lane >> 2;
    const uint32_t park = sb + SM_PARK + w * 65536 + ww * 2048 + lane * 16;
    const uint32_t lm_off = ((lane & 7) + ((lane >> 4) << 3)) * 128 + (((2 * ww + ((lane >> 3) & 1)) ^ (lane & 7)) << 4);
    uint32_t X[144];
    {
      float sA[4] = {0, 0, 0, 0}, sB[4] = {0, 0, 0, 0}, qa[4] = {0, 0, 0, 0}, qb[4] = {0, 0, 0, 0}, qc[4] = {0, 0, 0, 0}, qd[4] = {0, 0, 0, 0};
#pragma unroll
      for (int j = 0; j < 9; j++) {
        mbar_wait(sb + SM_BAR + 8 * (B_HFULL + w * 9 + j), 0);
        const uint32_t box = (j < 8 ? sb + SM_PARK + w * 65536 + j * 8192 : sb + HBOX8_OFF + w * 8192) + lm_off;
#pragma unroll
        for (int k = 0; k < 4; k++) {
          uint32_t* x = X + 16 * j + 4 * k;
          ldsm4_t(box + k * 2048, x[0], x[1], x[2], x[3]);
        }
#pragma unroll
        for (int k = 0; k < 4; k++) {
          uint32_t* x = X + 16 * j + 4 * k;
          mma_bf16((k & 1) ? sB : sA, x[0], x[1], x[2], x[3], 0x3F803F80u, 0x3F803F80u);
          mma_bf16((k & 1) ? qc : qa, x[0], x[1], x[2], x[3], x[0], x[2]);
          mma_bf16((k & 1) ? qd : qb, x[0], x[1], x[2], x[3], x[1], x[3]);
        }
      }
      __syncwarp();
      if (lane == 0) mbar_arrive(sb + SM_BAR + 8 * B_HFREE);
      const float m0 = (sA[0] + sB[0]) * (1.0f / D_MODEL), m1 = (sA[2] + sB[2]) * (1.0f / D_MODEL);
      float d0 = (g & 1) ? qa[1] + qc[1] : qa[0] + qc[0];
      float d1 = (g & 1) ? qb[3] + qd[3] : qb[2] + qd[2];
      d0 = __shfl_sync(0xffffffffu, d0, g * 4 + (g >> 1));
      d1 = __shfl_sync(0xffffffffu, d1, g * 4 + (g >> 1));
      const float v0 = fmaxf(d0 * (1.0f / D_MODEL) - m0 * m0, 0.f), v1 = fmaxf(d1 * (1.0f / D_MODEL) - m1 * m1, 0.f);
      const float sd0 = rbf(sqrtf(rbf(rbf(v0) + 1e-5f))), sd1 = rbf(sqrtf(rbf(rbf(v1) + 1e-5f)));
      const float p0 = __uint_as_float(0x7F000000u - (__float_as_uint(sd0) & 0x7F800000u));
      const float p1 = __uint_as_float(0x7F000000u - (__float_as_uint(sd1) & 0x7F800000u));
      const float f0 = 1.0f / (sd0 * p0), f1 = 1.0f / (sd1 * p1);
      if ((lane & 3) == 0) { s_r2[w * 64 + ww * 16 + g] = f0 * f0; s_r2[w * 64 + ww * 16 + g + 8] = f1 * f1; }
      const uint32_t pp0 = pack_bf16(p0, p0), pp1 = pack_bf16(p1, p1);
      const float n0 = -rbf(m0) * p0, n1 = -rbf(m1) * p1;
      const uint32_t mm0 = pack_bf16(n0, n0), mm1 = pack_bf16(n1, n1);
#pragma unroll
      for (int i = 0; i < 144; i++) X[i] = fma_bf16x2(X[i], (i & 1) ? pp1 : pp0, (i & 1) ? mm1 : mm0);
      wg_bar(w);
    }
    TS(1, tid == 0); TS(6, tid == 128);
    Ring rg{0, 0};
    int prev_st = 0;
    uint32_t H[144];
    {
      float acc[64];
      mbar_wait(sb + SM_BAR + 8 * (B_FULL + rg.st), rg.ph);
#pragma unroll 1
      for (int c = 0;; c++) {
        reg_fence<64>(acc);
#pragma unroll
        for (int s = 0; s < NST1; s++) {
          const uint64_t db = mkdesc(sb + SM_RING + rg.st * STAGE_BYTES, STAGE_BYTES / 2, 1024, 1);
          const int cur_st = rg.st;
#pragma unroll
          for (int k = 0; k < KS1; k++) {
            const int kk = 4 * (s * KS1 + k);
            if (k == KS1 - 1) {
              ring_next(rg);
              mbar_wait(sb + SM_BAR + 8 * (B_FULL + rg.st), rg.ph);
            }
            wg_fence();
            wgmma_rs_n128_tb(acc, X[kk], X[kk + 1], X[kk + 2], X[kk + 3], db + k * 128, (s | k) != 0);
            wg_commit();
            if (k == REL_K && s > 0) {
              wg_wait<REL_K + 1>();
              if (lane == 0) mbar_arrive(sb + SM_BAR + 8 * (B_EMPTY + prev_st));
            }
          }
          prev_st = cur_st;
        }
        wg_wait<0>();
        if (lane == 0) mbar_arrive(sb + SM_BAR + 8 * (B_EMPTY + prev_st));
        reg_fence<64>(acc);
        if (c == 8) break;
#pragma unroll
        for (int q = 0; q < 4; q++)
          sts128(park + c * 8192 + q * 512, reglu2(acc + 8 * q), reglu2(acc + 8 * q + 2), reglu2(acc + 8 * q + 4),
                 reglu2(acc + 8 * q + 6));
      }
      TS(2, tid == 0); TS(7, tid == 128);
#pragma unroll
      for (int i = 0; i < 16; i++) H[i] = reglu2(acc + 2 * i);
#pragma unroll
      for (int i = 0; i < 32; i++) lds128(park + (i >> 2) * 8192 + (i & 3) * 512, H[16 + 4 * i], H[17 + 4 * i], H[18 + 4 * i], H[19 + 4 * i]);
    }
    float a0[32], a1[32];
    const uint32_t stf = sb + SM_BAR + 8 * (B_STFULL + w * 8);
    TS(22 + w, (tid & 127) == 0);
    down_step<false>(a0, a1, H, rg, prev_st, sb, 0, 0, lane);
#pragma unroll 1
    for (int p = 0; p < 4; p++) {
      TS(24 + 4 * p + w, (tid & 127) == 0);
      down_step<true>(a1, a0, H, rg, prev_st, sb, park + (2 * p) * 8192, stf + 16 * p, lane);
      TS(26 + 4 * p + w, (tid & 127) == 0);
      down_step<true>(a0, a1, H, rg, prev_st, sb, park + (2 * p + 1) * 8192, stf + 16 * p + 8, lane);
    }
    wg_wait<0>();
    reg_fence<32>(a0);
    TS(3, tid == 0); TS(8, tid == 128);
    const int base = (mt * 9 + fs) * 8;
    if (lane < 8 && lane != fs) wait_flag(&g_flag[(base + lane) * 2 + w], epoch);
    __syncwarp();
    TS(4, tid == 0); TS(9, tid == 128);
#pragma unroll
    for (int i = 1; i < 8; i++) {
      const uint4* p = g_part + (size_t)((base + (fs ^ i)) * 2 + w) * 512 + ww * 128 + lane;
#pragma unroll
      for (int q = 0; q < 4; q++) {
        const uint4 v = ldg_cg(p + q * 32);
        H[16 * i + 4 * q] = v.x; H[16 * i + 4 * q + 1] = v.y; H[16 * i + 4 * q + 2] = v.z; H[16 * i + 4 * q + 3] = v.w;
      }
    }
    if (w == 1) ring_next(rg);
    mbar_wait(sb + SM_BAR + 8 * (B_FULL + rg.st), rg.ph);
#pragma unroll
    for (int k = 0; k < 4; k++) ldsm4_t(sb + SM_RING + rg.st * STAGE_BYTES + lm_off + k * 2048, H[4 * k], H[4 * k + 1], H[4 * k + 2], H[4 * k + 3]);
#pragma unroll
    for (int i = 1; i < 8; i++)
#pragma unroll
      for (int j = 0; j < 16; j++) { a0[2 * j] += bf_lo(H[16 * i + j]); a0[2 * j + 1] += bf_hi(H[16 * i + j]); }
    const float r2a = s_r2[w * 64 + ww * 16 + g], r2b = s_r2[w * 64 + ww * 16 + g + 8];
#pragma unroll
    for (int j = 0; j < 16; j++) {
      a0[2 * j] = fmaf(a0[2 * j], (j & 1) ? r2b : r2a, bf_lo(H[j]));
      a0[2 * j + 1] = fmaf(a0[2 * j + 1], (j & 1) ? r2b : r2a, bf_hi(H[j]));
    }
    uint32_t* o = (uint32_t*)(out + (size_t)(mt * 128 + w * 64 + ww * 16 + g) * D_MODEL + fs * 64 + 2 * (lane & 3));
#pragma unroll
    for (int j = 0; j < 16; j++) o[(j & 1) * (8 * D_MODEL / 2) + (j >> 1) * 4] = pack_bf16(a0[2 * j], a0[2 * j + 1]);
    TS(5, tid == 0); TS(10, tid == 128);
    TS_DUMP();
  }
}

typedef CUresult (*EncodeFn)(CUtensorMap*, CUtensorMapDataType, cuuint32_t, void*, const cuuint64_t*, const cuuint64_t*,
                             const cuuint32_t*, const cuuint32_t*, CUtensorMapInterleave, CUtensorMapSwizzle,
                             CUtensorMapL2promotion, CUtensorMapFloatOOBfill);
static void make_map(EncodeFn enc, CUtensorMap* m, const void* ptr, uint64_t cols, uint64_t rows, uint32_t bc, uint32_t br,
                     CUtensorMapSwizzle swz) {
  cuuint64_t dims[2] = {cols, rows};
  cuuint64_t strides[1] = {cols * 2};
  cuuint32_t box[2] = {bc, br};
  cuuint32_t es[2] = {1, 1};
  enc(m, CU_TENSOR_MAP_DATA_TYPE_BFLOAT16, 2, (void*)ptr, dims, strides, box, es, CU_TENSOR_MAP_INTERLEAVE_NONE, swz,
      CU_TENSOR_MAP_L2_PROMOTION_L2_128B, CU_TENSOR_MAP_FLOAT_OOB_FILL_NONE);
}

extern "C" void kernel_launch(void* const* d_in, const int* in_sizes, int n_in, void* d_out, int out_size) {
  static EncodeFn enc = nullptr;
  static void* hT = nullptr;
  if (!enc) {
    void* fn = nullptr; cudaDriverEntryPointQueryResult qr;
    cudaGetDriverEntryPoint("cuTensorMapEncodeTiled", &fn, cudaEnableDefault, &qr);
    enc = (EncodeFn)fn;
    cudaGetSymbolAddress(&hT, g_hT);
    cudaFuncSetAttribute(fused_kernel, cudaFuncAttributeMaxDynamicSharedMemorySize, SMEM_BYTES);
  }
  CUtensorMap tmWg, tmWu, tmWd, tmHT;
  make_map(enc, &tmWg, d_in[10], F_FFN, D_MODEL, 64, KS1 * 16, CU_TENSOR_MAP_SWIZZLE_128B);
  make_map(enc, &tmWu, d_in[11], F_FFN, D_MODEL, 64, KS1 * 16, CU_TENSOR_MAP_SWIZZLE_128B);
  make_map(enc, &tmWd, d_in[12], D_MODEL, F_FFN, 64, KS2 * 16, CU_TENSOR_MAP_SWIZZLE_128B);
  make_map(enc, &tmHT, hT, L_SEQ, D_MODEL, 64, 64, CU_TENSOR_MAP_SWIZZLE_128B);
  typedef const uint16_t* up;
  SsmPtrs P{(up)d_in[0], (up)d_in[1], (up)d_in[2], (up)d_in[3], (up)d_in[4], (up)d_in[5], (up)d_in[6], (up)d_in[7], (up)d_in[8],
            (const uint8_t*)d_in[10], (const uint8_t*)d_in[11], (const uint8_t*)d_in[12]};
  fused_kernel<<<NCTA, NTHREADS, SMEM_BYTES>>>(tmWg, tmWu, tmWd, tmHT, P, (__nv_bfloat16*)d_out);
}
```

```cpp
#include <cuda_runtime.h>
#include <cuda_bf16.h>
#include <cuda.h>
#include <stdint.h>
#include <type_traits>

constexpr int L_SEQ = 2048, D_MODEL = 576, N_STATE = 128, F_FFN = 4608;
constexpr int NCTA = 128;
constexpr int NTHREADS = 384;

constexpr int KS1 = 3;
constexpr int KS2 = 2 * KS1;
constexpr int NST1 = 36 / KS1;
constexpr int NST2 = 36 / KS2;
constexpr int STAGE_BYTES = KS1 * 16 * 128 * 2;
constexpr int SKEW = 3;
constexpr int HEAD = 4;
constexpr int RING_BYTES = 98304;
constexpr int NSTAGE = RING_BYTES / STAGE_BYTES;
constexpr int SM_PARK = 0;
constexpr int SM_RING = 131072;
constexpr int SM_BAR = SM_RING + RING_BYTES;
constexpr int SMEM_BYTES = SM_BAR + 3072;
constexpr int HBOX8_OFF = SM_RING + RING_BYTES - 16384;
constexpr int HBOX8_STAGE = (RING_BYTES - 16384) / STAGE_BYTES;

constexpr int C_U = 0;
constexpr int C_X = 4608;
constexpr int C_Y0 = 8704;
constexpr int C_Y1 = C_Y0 + 4096;
constexpr int C_YF = C_Y1 + 4096;
constexpr int C_Y3 = C_YF + 3072;
constexpr int C_PE = C_Y3 + 2048;
constexpr int C_PO = C_PE + 1344;
constexpr int C_T2 = C_PO + 1280;
constexpr int C_T3 = C_T2 + 768;
constexpr int C_MISC = C_T3 + 512;
constexpr int CHS = 26112;
constexpr int SM_LN = SM_BAR - 36864;
constexpr int SM_QP = SM_RING;
constexpr int SM_LNP = SM_QP + 5 * 10240;
constexpr int SM_STAT = SM_LNP + 2560;
static_assert(C_MISC + 16 <= CHS && CHS % 512 == 0 && 5 * CHS <= SM_RING && SM_LN >= SM_STAT && SM_STAT + 12288 <= SM_BAR, "smem map");
__host__ __device__ constexpr int hbox_off(int w, int j) {
  return j == 0 ? HBOX8_OFF + w * 8192 : SM_PARK + (j < 4 ? 3 * w + j - 1 : 2 + 5 * w + j) * 8192;
}
static_assert(6 * 8192 <= 2 * CHS, "smem map");
__device__ __forceinline__ int gch(int c) {
  const int b = blockIdx.x;
  return 128 * c + (b >> (c >> 2));
}

constexpr int B_FULL = 0;
constexpr int B_EMPTY = B_FULL + NSTAGE;
constexpr int B_HFULL = B_EMPTY + NSTAGE;
constexpr int B_HFREE = B_HFULL + 18;
constexpr int B_PRO = B_HFREE + 1;
constexpr int B_C8 = B_PRO + 1;
constexpr int B_IN = B_C8 + 1;
constexpr int B_IN6 = B_IN + 2;
constexpr int B_SQ = B_IN6 + 1;
constexpr int B_XS = B_SQ + 2;
constexpr int B_PEER = B_XS + 1;
constexpr int B_ST1 = B_PEER + 2;
constexpr int B_EP = B_ST1 + 7;
constexpr int B_MM = B_EP + 1;
constexpr int B_COUNT = B_MM + 5;
constexpr int SM_CS = SM_BAR + 640;
constexpr int B_LN = B_COUNT;

static_assert(8 * (B_LN + 2) <= 640, "smem map");

__device__ __align__(1024) __nv_bfloat16 g_hT[D_MODEL * L_SEQ];
__device__ __align__(1024) uint4 g_part[16 * 9 * 8 * 1024];
__device__ unsigned int g_flag[16 * 9 * 8];
__device__ __align__(128) uint2 g_sq[L_SEQ * 8];
__device__ unsigned int g_epoch;
__device__ __align__(1024) uint4 g_xT[D_MODEL * 256];
__device__ __align__(128) uint4 g_stat[768];
__device__ unsigned int g_done[96];

__device__ __forceinline__ uint32_t smem_u32(const void* p) { return (uint32_t)__cvta_generic_to_shared(p); }
__device__ __forceinline__ void mbar_init(uint32_t bar, int cnt) { asm volatile("mbarrier.init.shared::cta.b64 [%0], %1;" ::"r"(bar), "r"(cnt)); }
__device__ __forceinline__ void mbar_expect_tx(uint32_t bar, uint32_t bytes) { asm volatile("mbarrier.arrive.expect_tx.shared::cta.b64 _, [%0], %1;" ::"r"(bar), "r"(bytes) : "memory"); }
__device__ __forceinline__ void mbar_arrive(uint32_t bar) { asm volatile("mbarrier.arrive.shared::cta.b64 _, [%0];" ::"r"(bar) : "memory"); }
__device__ __forceinline__ void mbar_wait(uint32_t bar, uint32_t parity) {
  asm volatile(
      "{\n.reg .pred p, q;\n.reg .u32 it;\n"
      "mbarrier.try_wait.parity.shared::cta.b64 p, [%0], %1;\n"
      "@p bra MW_DONE_%=;\n"
      "mov.u32 it, 0;\n"
      "MW_LOOP_%=:\n"
      "mbarrier.try_wait.parity.shared::cta.b64 p, [%0], %1;\n"
      "@p bra MW_DONE_%=;\n"
      "add.u32 it, it, 1;\n"
      "setp.gt.u32 q, it, 4194304;\n"
      "@q trap;\n"
      "bra MW_LOOP_%=;\n"
      "MW_DONE_%=:\n}\n" ::"r"(bar), "r"(parity) : "memory");
}
__device__ __forceinline__ void mbar_spin(uint32_t bar, uint32_t parity) {
  asm volatile("{\n.reg .pred p;\nMS_LOOP_%=:\nmbarrier.try_wait.parity.shared::cta.b64 p, [%0], %1;\n@!p bra MS_LOOP_%=;\n}\n"
               ::"r"(bar), "r"(parity) : "memory");
}
__device__ __forceinline__ void mbar_wait_long(uint32_t bar, uint32_t parity) {
  asm volatile(
      "{\n.reg .pred p, q;\n.reg .u32 it;\n"
      "mov.u32 it, 0;\n"
      "ML_LOOP_%=:\n"
      "mbarrier.try_wait.parity.shared::cta.b64 p, [%0], %1, %2;\n"
      "@p bra ML_DONE_%=;\n"
      "add.u32 it, it, 1;\n"
      "setp.gt.u32 q, it, 1048576;\n"
      "@q trap;\n"
      "bra ML_LOOP_%=;\n"
      "ML_DONE_%=:\n}\n" ::"r"(bar), "r"(parity), "r"(4000) : "memory");
}
__device__ __forceinline__ void mbar_wait_cluster(uint32_t bar, uint32_t parity) {
  asm volatile(
      "{\n.reg .pred p, q;\n.reg .u32 it;\n"
      "mov.u32 it, 0;\n"
      "MC_LOOP_%=:\n"
      "mbarrier.try_wait.parity.acquire.cluster.shared::cta.b64 p, [%0], %1;\n"
      "@p bra MC_DONE_%=;\n"
      "add.u32 it, it, 1;\n"
      "setp.gt.u32 q, it, 4194304;\n"
      "@q trap;\n"
      "bra MC_LOOP_%=;\n"
      "MC_DONE_%=:\n}\n" ::"r"(bar), "r"(parity) : "memory");
}
__device__ __forceinline__ uint32_t peer_addr(uint32_t a) {
  uint32_t r; asm("mapa.shared::cluster.u32 %0, %1, %2;" : "=r"(r) : "r"(a), "r"((blockIdx.x & 1) ^ 1)); return r;
}
__device__ __forceinline__ void mbar_arrive_peer(uint32_t bar) {
  asm volatile("mbarrier.arrive.shared::cluster.b64 _, [%0];" ::"r"(peer_addr(bar)) : "memory");
}
__device__ __forceinline__ void tma_load_2d(uint32_t dst, const CUtensorMap* tm, int c0, int c1, uint32_t bar) {
  asm volatile("cp.async.bulk.tensor.2d.shared::cluster.global.mbarrier::complete_tx::bytes [%0], [%1, {%3, %4}], [%2];"
               ::"r"(dst), "l"(tm), "r"(bar), "r"(c0), "r"(c1) : "memory");
}
__device__ __forceinline__ bool elect_one() {
  uint32_t r;
  asm volatile("{\n.reg .pred p;\nelect.sync _|p, 0xffffffff;\nselp.u32 %0, 1, 0, p;\n}\n" : "=r"(r));
  return r != 0;
}
__device__ __forceinline__ void tma_load_2d_pair(uint32_t dst, const CUtensorMap* tm, int c0, int c1, uint32_t bar) {
  asm volatile("cp.async.bulk.tensor.2d.shared::cluster.global.mbarrier::complete_tx::bytes.multicast::cluster [%0], [%1, {%3, %4}], [%2], %5;"
               ::"r"(dst), "l"(tm), "r"(bar), "r"(c0), "r"(c1), "h"((uint16_t)3) : "memory");
}
__device__ __forceinline__ void bulk_store(void* dst, uint32_t src, uint32_t bytes) {
  asm volatile("cp.async.bulk.global.shared::cta.bulk_group [%0], [%1], %2;" ::"l"(dst), "r"(src), "r"(bytes) : "memory");
}
__device__ __forceinline__ void bulk_load(uint32_t dst, const void* src, uint32_t bytes, uint32_t bar) {
  asm volatile("cp.async.bulk.shared::cluster.global.mbarrier::complete_tx::bytes [%0], [%1], %2, [%3];" ::"r"(dst), "l"(src), "r"(bytes), "r"(bar) : "memory");
}
__device__ __forceinline__ void bulk_commit() { asm volatile("cp.async.bulk.commit_group;" ::: "memory"); }
__device__ __forceinline__ void bulk_wait0() { asm volatile("cp.async.bulk.wait_group 0;" ::: "memory"); }
__device__ __forceinline__ void fence_async_smem() { asm volatile("fence.proxy.async.shared::cta;" ::: "memory"); }
__device__ __forceinline__ void fence_async_global() { asm volatile("fence.proxy.async.global;" ::: "memory"); }
__device__ __forceinline__ void wg_fence() { asm volatile("wgmma.fence.sync.aligned;" ::: "memory"); }
__device__ __forceinline__ void wg_commit() { asm volatile("wgmma.commit_group.sync.aligned;" ::: "memory"); }
template <int N> __device__ __forceinline__ void wg_wait() { asm volatile("wgmma.wait_group.sync.aligned %0;" ::"n"(N) : "memory"); }
template <int N> __device__ __forceinline__ void reg_fence(float* d) {
#pragma unroll
  for (int i = 0; i < N; i++) asm volatile("" : "+f"(d[i])::"memory");
}
__device__ __forceinline__ uint64_t mkdesc(uint32_t addr, uint32_t lbo, uint32_t sbo, uint32_t swz) {
  return (uint64_t)((addr & 0x3FFFF) >> 4) | ((uint64_t)(lbo >> 4) << 16) | ((uint64_t)(sbo >> 4) << 32) | ((uint64_t)swz << 62);
}
__device__ __forceinline__ void ldsm4_t(uint32_t addr, uint32_t& r0, uint32_t& r1, uint32_t& r2, uint32_t& r3) {
  asm volatile("ldmatrix.sync.aligned.m8n8.x4.trans.shared.b16 {%0,%1,%2,%3}, [%4];" : "=r"(r0), "=r"(r1), "=r"(r2), "=r"(r3) : "r"(addr) : "memory");
}
__device__ __forceinline__ void ldsm4(uint32_t addr, uint32_t& r0, uint32_t& r1, uint32_t& r2, uint32_t& r3) {
  asm volatile("ldmatrix.sync.aligned.m8n8.x4.shared.b16 {%0,%1,%2,%3}, [%4];" : "=r"(r0), "=r"(r1), "=r"(r2), "=r"(r3) : "r"(addr) : "memory");
}
__device__ __forceinline__ void mma_bf16(float* c, uint32_t a0, uint32_t a1, uint32_t a2, uint32_t a3, uint32_t b0, uint32_t b1) {
  asm volatile("mma.sync.aligned.m16n8k16.row.col.f32.bf16.bf16.f32 {%0,%1,%2,%3}, {%4,%5,%6,%7}, {%8,%9}, {%0,%1,%2,%3};"
               : "+f"(c[0]), "+f"(c[1]), "+f"(c[2]), "+f"(c[3]) : "r"(a0), "r"(a1), "r"(a2), "r"(a3), "r"(b0), "r"(b1));
}
__device__ __forceinline__ void mma_bf16_z(float* d, uint32_t a0, uint32_t a1, uint32_t a2, uint32_t a3, uint32_t b0, uint32_t b1, const float4& z) {
  asm volatile("mma.sync.aligned.m16n8k16.row.col.f32.bf16.bf16.f32 {%0,%1,%2,%3}, {%4,%5,%6,%7}, {%8,%9}, {%10,%11,%12,%13};"
               : "=f"(d[0]), "=f"(d[1]), "=f"(d[2]), "=f"(d[3])
               : "r"(a0), "r"(a1), "r"(a2), "r"(a3), "r"(b0), "r"(b1), "f"(z.x), "f"(z.y), "f"(z.z), "f"(z.w));
}
__device__ __forceinline__ void mma_bf16_k8(float* c, uint32_t a0, uint32_t a1, uint32_t b0) {
  asm volatile("mma.sync.aligned.m16n8k8.row.col.f32.bf16.bf16.f32 {%0,%1,%2,%3}, {%4,%5}, {%6}, {%0,%1,%2,%3};"
               : "+f"(c[0]), "+f"(c[1]), "+f"(c[2]), "+f"(c[3]) : "r"(a0), "r"(a1), "r"(b0));
}
__device__ __forceinline__ uint32_t pack_bf16(float lo, float hi) {
  uint32_t r; asm("cvt.rn.bf16x2.f32 %0, %1, %2;" : "=r"(r) : "f"(hi), "f"(lo)); return r;
}
__device__ __forceinline__ float bf_lo(uint32_t v) { return __uint_as_float(v << 16); }
__device__ __forceinline__ float bf_hi(uint32_t v) { return __uint_as_float(v & 0xFFFF0000u); }
__device__ __forceinline__ float rbf(float x) { return __bfloat162float(__float2bfloat16(x)); }
__device__ __forceinline__ uint32_t sub_bf16x2(uint32_t a, uint32_t b) {
  uint32_t r; asm("sub.rn.bf16x2 %0, %1, %2;" : "=r"(r) : "r"(a), "r"(b)); return r;
}
__device__ __forceinline__ void sts128(uint32_t addr, uint32_t a, uint32_t b, uint32_t c, uint32_t d) {
  asm volatile("st.shared.v4.b32 [%0], {%1,%2,%3,%4};" ::"r"(addr), "r"(a), "r"(b), "r"(c), "r"(d) : "memory");
}
__device__ __forceinline__ void lds128(uint32_t addr, uint32_t& a, uint32_t& b, uint32_t& c, uint32_t& d) {
  asm volatile("ld.shared.v4.b32 {%0,%1,%2,%3}, [%4];" : "=r"(a), "=r"(b), "=r"(c), "=r"(d) : "r"(addr) : "memory");
}
__device__ __forceinline__ void st_release(unsigned* p, unsigned v) {
  asm volatile("st.release.gpu.global.u32 [%0], %1;" ::"l"(p), "r"(v) : "memory");
}
__device__ __forceinline__ void wait_flag(const unsigned* p, unsigned epoch) {
  asm volatile(
      "{\n.reg .pred p, q;\n.reg .u32 it, v;\n.reg .s32 d;\n"
      "mov.u32 it, 0;\n"
      "WF_LOOP_%=:\n"
      "ld.acquire.gpu.global.u32 v, [%0];\n"
      "sub.s32 d, v, %1;\n"
      "setp.ge.s32 p, d, 0;\n"
      "@p bra WF_DONE_%=;\n"
      "add.u32 it, it, 1;\n"
      "setp.gt.u32 q, it, 4194304;\n"
      "@q trap;\n"
      "bra WF_LOOP_%=;\n"
      "WF_DONE_%=:\n}\n" ::"l"(p), "r"(epoch) : "memory");
}
#define named_bar(id, n) asm volatile("bar.sync %0, %1;" ::"n"(id), "n"(n) : "memory")

__device__ __forceinline__ void wg_bar(int wgi) { asm volatile("bar.sync %0, 128;" ::"r"(wgi + 1) : "memory"); }
__device__ __forceinline__ void stsm4(uint32_t addr, uint32_t r0, uint32_t r1, uint32_t r2, uint32_t r3) {
  asm volatile("stmatrix.sync.aligned.m8n8.x4.shared.b16 [%0], {%1,%2,%3,%4};" ::"r"(addr), "r"(r0), "r"(r1), "r"(r2), "r"(r3) : "memory");
}
__device__ __forceinline__ void stsm4_t(uint32_t addr, uint32_t r0, uint32_t r1, uint32_t r2, uint32_t r3) {
  asm volatile("stmatrix.sync.aligned.m8n8.x4.trans.shared.b16 [%0], {%1,%2,%3,%4};" ::"r"(addr), "r"(r0), "r"(r1), "r"(r2), "r"(r3) : "memory");
}
__device__ __forceinline__ float4 lds_f4(uint32_t addr) {
  float4 v; asm volatile("ld.shared.v4.f32 {%0,%1,%2,%3}, [%4];" : "=f"(v.x), "=f"(v.y), "=f"(v.z), "=f"(v.w) : "r"(addr) : "memory"); return v;
}
__device__ __forceinline__ float2 lds_f2(uint32_t addr) {
  float2 v; asm volatile("ld.shared.v2.f32 {%0,%1}, [%2];" : "=f"(v.x), "=f"(v.y) : "r"(addr) : "memory"); return v;
}
__device__ __forceinline__ void sts_f2(uint32_t addr, float a, float b) {
  asm volatile("st.shared.v2.f32 [%0], {%1,%2};" ::"r"(addr), "f"(a), "f"(b) : "memory");
}
__device__ __forceinline__ void sts64(uint32_t addr, uint32_t a, uint32_t b) {
  asm volatile("st.shared.v2.b32 [%0], {%1,%2};" ::"r"(addr), "r"(a), "r"(b) : "memory");
}
__device__ __forceinline__ void lds64(uint32_t addr, uint32_t& a, uint32_t& b) {
  asm volatile("ld.shared.v2.b32 {%0,%1}, [%2];" : "=r"(a), "=r"(b) : "r"(addr) : "memory");
}
__device__ __forceinline__ uint32_t lds32(uint32_t addr) {
  uint32_t v; asm volatile("ld.shared.b32 %0, [%1];" : "=r"(v) : "r"(addr) : "memory"); return v;
}
__device__ __forceinline__ void sts32(uint32_t addr, uint32_t v) { asm volatile("st.shared.b32 [%0], %1;" ::"r"(addr), "r"(v) : "memory"); }
__device__ __forceinline__ void sts16(uint32_t addr, uint32_t v) { asm volatile("st.shared.u16 [%0], %1;" ::"r"(addr), "h"((uint16_t)v) : "memory"); }
__device__ __forceinline__ uint32_t add_bf16x2(uint32_t a, uint32_t b) { uint32_t r; asm("add.rn.bf16x2 %0, %1, %2;" : "=r"(r) : "r"(a), "r"(b)); return r; }
__device__ __forceinline__ uint32_t mul_bf16x2(uint32_t a, uint32_t b) { uint32_t r; asm("mul.rn.bf16x2 %0, %1, %2;" : "=r"(r) : "r"(a), "r"(b)); return r; }
__device__ __forceinline__ uint32_t movm(uint32_t v) {
  uint32_t r; asm volatile("movmatrix.sync.aligned.m8n8.trans.b16 %0, %1;" : "=r"(r) : "r"(v)); return r;
}
__device__ __forceinline__ void st_global(uint4* p, uint32_t a, uint32_t b, uint32_t c, uint32_t d) {
  asm volatile("st.global.v4.u32 [%0], {%1,%2,%3,%4};" ::"l"(p), "r"(a), "r"(b), "r"(c), "r"(d) : "memory");
}
__device__ __forceinline__ float rcp_fast(float x) { float r; asm("rcp.approx.ftz.f32 %0, %1;" : "=f"(r) : "f"(x)); return r; }
struct cplx { float r, i; };
__device__ __forceinline__ cplx cmul(cplx a, cplx b) { return {fmaf(a.r, b.r, -(a.i * b.i)), fmaf(a.r, b.i, a.i * b.r)}; }
__device__ __forceinline__ cplx csq(cplx a) {
  float im;
  asm("{\n.reg .f32 u;\nmul.f32 u, %1, %2;\nmul.f32 %0, u, 0f40000000;\n}" : "=f"(im) : "f"(a.r), "f"(a.i));
  return {fmaf(a.r, a.r, -(a.i * a.i)), im};
}
__device__ __forceinline__ cplx cpolar(float x, float a) {
  float m, sn, cs;
  asm("ex2.approx.ftz.f32 %0, %1;" : "=f"(m) : "f"(x));
  asm("sin.approx.ftz.f32 %0, %1;" : "=f"(sn) : "f"(a));
  asm("cos.approx.ftz.f32 %0, %1;" : "=f"(cs) : "f"(a));
  return {m * cs, m * sn};
}
__device__ __forceinline__ cplx cexp_e(float zl, float zt, float e) {
  const float a = zt * e;
  return cpolar(zl * e, (a - rintf(a)) * 6.283185307179586f);
}

template <int OFF, int ACC>
__device__ __forceinline__ void wgmma_ring_n128(float* d, uint32_t a0, uint32_t a1, uint32_t a2, uint32_t a3, uint64_t dbase) {
  asm volatile("{\n.reg .b64 db;\nadd.u64 db, %68, %69;\n"
    "wgmma.mma_async.sync.aligned.m64n128k16.f32.bf16.bf16 "
    "{%0, %1, %2, %3, %4, %5, %6, %7, %8, %9, %10, %11, %12, %13, %14, %15, "
    "%16, %17, %18, %19, %20, %21, %22, %23, %24, %25, %26, %27, %28, %29, %30, %31, "
    "%32, %33, %34, %35, %36, %37, %38, %39, %40, %41, %42, %43, %44, %45, %46, %47, "
    "%48, %49, %50, %51, %52, %53, %54, %55, %56, %57, %58, %59, %60, %61, %62, %63}, "
    "{%64, %65, %66, %67}, db, %70, 1, 1, 1;\n}\n"
    : "+f"(d[0]), "+f"(d[1]), "+f"(d[2]), "+f"(d[3]), "+f"(d[4]), "+f"(d[5]), "+f"(d[6]), "+f"(d[7]),
      "+f"(d[8]), "+f"(d[9]), "+f"(d[10]), "+f"(d[11]), "+f"(d[12]), "+f"(d[13]), "+f"(d[14]), "+f"(d[15]),
      "+f"(d[16]), "+f"(d[17]), "+f"(d[18]), "+f"(d[19]), "+f"(d[20]), "+f"(d[21]), "+f"(d[22]), "+f"(d[23]),
      "+f"(d[24]), "+f"(d[25]), "+f"(d[26]), "+f"(d[27]), "+f"(d[28]), "+f"(d[29]), "+f"(d[30]), "+f"(d[31]),
      "+f"(d[32]), "+f"(d[33]), "+f"(d[34]), "+f"(d[35]), "+f"(d[36]), "+f"(d[37]), "+f"(d[38]), "+f"(d[39]),
      "+f"(d[40]), "+f"(d[41]), "+f"(d[42]), "+f"(d[43]), "+f"(d[44]), "+f"(d[45]), "+f"(d[46]), "+f"(d[47]),
      "+f"(d[48]), "+f"(d[49]), "+f"(d[50]), "+f"(d[51]), "+f"(d[52]), "+f"(d[53]), "+f"(d[54]), "+f"(d[55]),
      "+f"(d[56]), "+f"(d[57]), "+f"(d[58]), "+f"(d[59]), "+f"(d[60]), "+f"(d[61]), "+f"(d[62]), "+f"(d[63])
    : "r"(a0), "r"(a1), "r"(a2), "r"(a3), "l"(dbase), "n"(OFF), "n"(ACC));
}

template <int OFF, int ACC>
__device__ __forceinline__ void wgmma_ring_n64(float* d, uint32_t a0, uint32_t a1, uint32_t a2, uint32_t a3, uint64_t dbase) {
  asm volatile("{\n.reg .b64 db;\nadd.u64 db, %36, %37;\n"
    "wgmma.mma_async.sync.aligned.m64n64k16.f32.bf16.bf16 "
    "{%0, %1, %2, %3, %4, %5, %6, %7, %8, %9, %10, %11, %12, %13, %14, %15, "
    "%16, %17, %18, %19, %20, %21, %22, %23, %24, %25, %26, %27, %28, %29, %30, %31}, "
    "{%32, %33, %34, %35}, db, %38, 1, 1, 1;\n}\n"
    : "+f"(d[0]), "+f"(d[1]), "+f"(d[2]), "+f"(d[3]), "+f"(d[4]), "+f"(d[5]), "+f"(d[6]), "+f"(d[7]),
      "+f"(d[8]), "+f"(d[9]), "+f"(d[10]), "+f"(d[11]), "+f"(d[12]), "+f"(d[13]), "+f"(d[14]), "+f"(d[15]),
      "+f"(d[16]), "+f"(d[17]), "+f"(d[18]), "+f"(d[19]), "+f"(d[20]), "+f"(d[21]), "+f"(d[22]), "+f"(d[23]),
      "+f"(d[24]), "+f"(d[25]), "+f"(d[26]), "+f"(d[27]), "+f"(d[28]), "+f"(d[29]), "+f"(d[30]), "+f"(d[31])
    : "r"(a0), "r"(a1), "r"(a2), "r"(a3), "l"(dbase), "n"(OFF), "n"(ACC));
}

__device__ __forceinline__ void wgmma_rs_n64(float* d, uint32_t a0, uint32_t a1, uint32_t a2, uint32_t a3, uint64_t db, int scale_d) {
  asm volatile("{\n.reg .pred p;\nsetp.ne.b32 p, %37, 0;\n"
    "wgmma.mma_async.sync.aligned.m64n64k16.f32.bf16.bf16 "
    "{%0, %1, %2, %3, %4, %5, %6, %7, %8, %9, %10, %11, %12, %13, %14, %15, "
    "%16, %17, %18, %19, %20, %21, %22, %23, %24, %25, %26, %27, %28, %29, %30, %31}, "
    "{%32, %33, %34, %35}, %36, p, 1, 1, 0;\n}\n"
    : "+f"(d[0]), "+f"(d[1]), "+f"(d[2]), "+f"(d[3]), "+f"(d[4]), "+f"(d[5]), "+f"(d[6]), "+f"(d[7]),
      "+f"(d[8]), "+f"(d[9]), "+f"(d[10]), "+f"(d[11]), "+f"(d[12]), "+f"(d[13]), "+f"(d[14]), "+f"(d[15]),
      "+f"(d[16]), "+f"(d[17]), "+f"(d[18]), "+f"(d[19]), "+f"(d[20]), "+f"(d[21]), "+f"(d[22]), "+f"(d[23]),
      "+f"(d[24]), "+f"(d[25]), "+f"(d[26]), "+f"(d[27]), "+f"(d[28]), "+f"(d[29]), "+f"(d[30]), "+f"(d[31])
    : "r"(a0), "r"(a1), "r"(a2), "r"(a3), "l"(db), "r"(scale_d));
}

__device__ __forceinline__ void wgmma_rs_n24_f16_tb(float* d, uint32_t a0, uint32_t a1, uint32_t a2, uint32_t a3, uint64_t db, int scale_d) {
  asm volatile("{\n.reg .pred p;\nsetp.ne.b32 p, %17, 0;\n"
    "wgmma.mma_async.sync.aligned.m64n24k16.f32.f16.f16 "
    "{%0, %1, %2, %3, %4, %5, %6, %7, %8, %9, %10, %11}, "
    "{%12, %13, %14, %15}, %16, p, 1, 1, 1;\n}\n"
    : "+f"(d[0]), "+f"(d[1]), "+f"(d[2]), "+f"(d[3]), "+f"(d[4]), "+f"(d[5]), "+f"(d[6]), "+f"(d[7]),
      "+f"(d[8]), "+f"(d[9]), "+f"(d[10]), "+f"(d[11])
    : "r"(a0), "r"(a1), "r"(a2), "r"(a3), "l"(db), "r"(scale_d));
}


__device__ __forceinline__ uint32_t reglu2(const float* a) {
  uint32_t g, u, r;
  asm("cvt.rn.relu.bf16x2.f32 %0, %1, %2;" : "=r"(g) : "f"(a[1]), "f"(a[0]));
  asm("cvt.rn.bf16x2.f32 %0, %1, %2;" : "=r"(u) : "f"(a[33]), "f"(a[32]));
  asm("mul.rn.bf16x2 %0, %1, %2;" : "=r"(r) : "r"(g), "r"(u));
  return r;
}
__device__ __forceinline__ uint32_t fma_bf16x2(uint32_t a, uint32_t b, uint32_t c) {
  uint32_t r; asm("fma.rn.bf16x2 %0, %1, %2, %3;" : "=r"(r) : "r"(a), "r"(b), "r"(c)); return r;
}
__device__ __forceinline__ int step_chunk(int f, int s) { return s == 0 ? 8 : (f ^ (8 - s)); }


struct RawPair { uint32_t are, aim, bre, bim, cre, cim; uint16_t ldt, dsk; };
__device__ __forceinline__ float bfu(uint16_t v) { return __uint_as_float((uint32_t)v << 16); }
__device__ __forceinline__ uint32_t pack_f16(float lo, float hi) {
  uint32_t r; asm("cvt.rn.f16x2.f32 %0, %1, %2;" : "=r"(r) : "f"(hi), "f"(lo)); return r;
}
__device__ __forceinline__ uint32_t hmul2(uint32_t a, uint32_t b) { uint32_t r; asm("mul.rn.f16x2 %0, %1, %2;" : "=r"(r) : "r"(a), "r"(b)); return r; }
__device__ __forceinline__ uint32_t hfma2(uint32_t a, uint32_t b, uint32_t c) { uint32_t r; asm("fma.rn.f16x2 %0, %1, %2, %3;" : "=r"(r) : "r"(a), "r"(b), "r"(c)); return r; }
__device__ __forceinline__ uint32_t hfms2(uint32_t a, uint32_t b, uint32_t c) {
  uint32_t r; asm("{\n.reg .b32 n;\nneg.f16x2 n, %3;\nfma.rn.f16x2 %0, %1, %2, n;\n}" : "=r"(r) : "r"(a), "r"(b), "r"(c)); return r;
}
__device__ __forceinline__ void store_powers(uint32_t dst, cplx b0, cplx b1) {
  cplx p[2][8];
#pragma unroll
  for (int e = 0; e < 2; e++) {
    p[e][1] = e ? b1 : b0;
    p[e][2] = csq(p[e][1]); p[e][3] = cmul(p[e][2], p[e][1]); p[e][4] = csq(p[e][2]);
    p[e][5] = cmul(p[e][4], p[e][1]); p[e][6] = csq(p[e][3]); p[e][7] = cmul(p[e][6], p[e][1]);
  }
  sts128(dst, 0x3C003C00u, 0u, pack_f16(p[0][1].r, p[1][1].r), pack_f16(p[0][1].i, p[1][1].i));
#pragma unroll
  for (int j = 1; j < 4; j++)
    sts128(dst + j * 64, pack_f16(p[0][2 * j].r, p[1][2 * j].r), pack_f16(p[0][2 * j].i, p[1][2 * j].i),
           pack_f16(p[0][2 * j + 1].r, p[1][2 * j + 1].r), pack_f16(p[0][2 * j + 1].i, p[1][2 * j + 1].i));
}

__device__ __forceinline__ void kgen_channel(const RawPair& p, uint32_t blk, uint32_t tQ, int wgi, int t, int flip) {
  const int lane = t & 31, ww = t >> 5, g = lane >> 2, tq = lane & 3;
  blk = __shfl_sync(0xffffffffu, blk, 0);
  const uint32_t tP = tQ + 5120, tB = blk + C_Y0;
  {
    const float dt = rbf(expf(bfu(p.ldt)));
    float zl[2], zt[2];
#pragma unroll
    for (int e = 0; e < 2; e++) {
      zl[e] = fmaxf(dt * (e ? bf_hi(p.are) : bf_lo(p.are)) * 1.4426950408889634f, -1e30f);
      zt[e] = dt * (e ? bf_hi(p.aim) : bf_lo(p.aim)) * 0.15915494309189535f;
      zt[e] -= rintf(zt[e]);
    }
    const int s = (t & 63) >> 2;
    if ((t ^ flip) < 64) {
      const int t = threadIdx.x & 63;
      store_powers(tQ + s * 320 + tq * 16, cpolar(zl[0] * 4.f, zt[0] * 25.132741228718345f), cpolar(zl[1] * 4.f, zt[1] * 25.132741228718345f));
      store_powers(tP + s * 320 + tq * 16, cexp_e(zl[0], zt[0], 32.f), cexp_e(zl[1], zt[1], 32.f));
      if (t < 52) sts128(blk + (t < 7 ? C_PE + 16 * t : t < 27 ? C_PE + 1136 + 16 * (t - 7) : C_PO + 1136 + 16 * (t - 27)), 0, 0, 0, 0);
      sts128(t < 32 ? blk + C_T2 + 512 + 16 * t : blk + C_U + 16 * (t - 32), 0, 0, 0, 0);
      if (t == 63) sts64(blk + C_MISC, p.dsk * 0x10001u, 0x3210u);
    } else {
      cplx c[2];
      c[0] = cmul({bf_lo(p.cre), bf_lo(p.cim)}, {dt * bf_lo(p.bre), dt * bf_lo(p.bim)});
      c[1] = cmul({bf_hi(p.cre), bf_hi(p.cim)}, {dt * bf_hi(p.bre), dt * bf_hi(p.bim)});
      const float mx = fmaxf(fmaxf(fabsf(c[0].r), fabsf(c[0].i)), fmaxf(fabsf(c[1].r), fabsf(c[1].i)));
      const uint32_t ex = max(__reduce_max_sync(0xffffffffu, __float_as_uint(mx)) >> 23, 16u);
      const float sc = __uint_as_float((262u - ex) << 23);
      if (lane == 0) sts32(blk + C_MISC + 8 + 4 * (ww & 1), (ex - 8u) << 23);
      if (s & 1) {
        float x = zl[0]; zl[0] = zl[1]; zl[1] = x;
        x = zt[0]; zt[0] = zt[1]; zt[1] = x;
        const cplx y = c[0]; c[0] = c[1]; c[1] = y;
      }
#pragma unroll
      for (int e = 0; e < 2; e++) {
        const cplx w1 = cpolar(zl[e], -zt[e] * 6.283185307179586f), w256 = cexp_e(zl[e], -zt[e], 256.f);
        const cplx w4 = csq(csq(w1));
        const cplx c0 = {c[e].r * sc, -c[e].i * sc};
        const cplx c1 = cmul(c0, w1), c2 = cmul(c1, w1), c3 = cmul(c2, w1), c4 = cmul(c0, w4);
        const cplx c256 = cmul(c0, w256), c258 = cmul(c2, w256), c260 = cmul(c4, w256);
        const cplx c512 = cmul(c256, w256), c516 = cmul(c260, w256), c768 = cmul(c512, w256), c772 = cmul(c516, w256);
        const cplx c1032 = cmul(cmul(c772, w4), w256), c1288 = cmul(c1032, w256), c1544 = cmul(c1288, w256), c1800 = cmul(c1544, w256);
        const uint32_t d = tB + s * 256 + (2 * tq + (e ^ (s & 1))) * 16;
        sts128(d, pack_f16(c2.r, c1.r), pack_f16(c4.r, c3.r), pack_f16(c258.r, c256.r), pack_f16(c260.r, c260.r));
        sts128(d + 128, pack_f16(c2.i, c1.i), pack_f16(c4.i, c3.i), pack_f16(c258.i, c256.i), pack_f16(c260.i, c260.i));
        sts128(d + 4096, pack_f16(c1.r, c0.r), pack_f16(c3.r, c2.r), pack_f16(c256.r, c256.r), pack_f16(c260.r, c258.r));
        sts128(d + 4224, pack_f16(c1.i, c0.i), pack_f16(c3.i, c2.i), pack_f16(c256.i, c256.i), pack_f16(c260.i, c258.i));
        sts128(d + 8192, pack_f16(c516.r, c512.r), pack_f16(c772.r, c768.r), pack_f16(c1032.r, c1288.r), pack_f16(c1544.r, c1800.r));
        sts128(d + 8320, pack_f16(c516.i, c512.i), pack_f16(c772.i, c768.i), pack_f16(c1032.i, c1288.i), pack_f16(c1544.i, c1800.i));
      }
    }
    fence_async_smem();
  }
  wg_bar(wgi);
  float acc[2][12];
  {
    const uint32_t rq = tQ + (g >> 1) * 64 + tq * 16 + (g & 1) * 8, rp = tP + ww * 64 + tq * 16;
    const uint64_t db = mkdesc(tB, 128, 4096, 0);
#pragma unroll
    for (int h = 0; h < 2; h++) {
      uint32_t A[8][4];
#pragma unroll
      for (int k = 0; k < 8; k++) {
        uint32_t qr, qi, lr, li, hr, hi;
        lds64(rq + (8 * h + k) * 320, qr, qi);
        lds128(rp + (8 * h + k) * 320, lr, li, hr, hi);
        A[k][0] = hfms2(lr, qr, hmul2(li, qi)); A[k][2] = hfma2(lr, qi, hmul2(li, qr));
        A[k][1] = hfms2(hr, qr, hmul2(hi, qi)); A[k][3] = hfma2(hr, qi, hmul2(hi, qr));
      }
      wg_fence();
#pragma unroll
      for (int k = 0; k < 8; k++) wgmma_rs_n24_f16_tb(acc[h], A[k][0], A[k][1], A[k][2], A[k][3], db + (8 * h + k) * 16, k != 0);
      wg_commit();
    }
  }
  const float2 us = lds_f2(blk + C_MISC + 8);
  wg_wait<0>();
  reg_fence<12>(acc[0]); reg_fence<12>(acc[1]);
  float v[12];
#pragma unroll
  for (int i = 0; i < 12; i++) v[i] = fmaf(acc[0][i], us.x, acc[1][i] * us.y);
  const int r = 16 * ww + g;
  const float t512 = __shfl_down_sync(0xffffffffu, v[2], 1);
  if (t == 126) v[2] -= t512;
  if (t == 127) { v[7] -= v[6]; v[2] = v[3] = v[6] = 0.f; }
  const uint32_t o = blk + 4 * (28 + 2 * r + (tq & 1) + 128 * (tq >> 1));
  sts32(o + C_PE + 4, pack_bf16(v[0], v[1]));
  sts32(o + C_PE + 68, pack_bf16(v[2], v[3]));
  sts32(o + C_PO, pack_bf16(v[4], v[5]));
  sts32(o + C_PO + 64, pack_bf16(v[6], v[7]));
  if (t == 0) sts32(blk + C_PE + 112, pack_bf16(v[5], 0.f));
  if (t == 125) sts32(blk + C_T2 + 512, pack_bf16(v[10], v[10]));
  if ((g & 1) == 0) {
    const uint32_t wl = pack_bf16(v[8], v[9]), wh = pack_bf16(v[10], v[11]);
    if (tq < 2) {
      const uint32_t f = blk + C_T2 + 4 * (64 + 32 * tq + (r >> 1));
      sts32(f, wl); sts32(f + 16, wh);
    } else {
      const uint32_t f = blk + C_T3 + 256 + 2 * ((64 * (tq - 2) + (r >> 1)) ^ 1);
      sts16(f, wl); sts16(f + 64, wl >> 16); sts16(f + 8, wh); sts16(f + 72, wh >> 16);
    }
  }
}

__device__ __forceinline__ uint32_t chunk_off(int a) { return (uint32_t)(a * 16) ^ (uint32_t)((a << 1) & 0x30); }
__device__ __forceinline__ uint32_t u_chunk(uint32_t blk, int a) { return blk + C_U + chunk_off(a + 32); }

__device__ __forceinline__ uint32_t word_off(int wi) { return (uint32_t)(wi << 2) ^ (uint32_t)((wi >> 1) & 0x30); }
__device__ __forceinline__ uint32_t band2(int c, int lo, int hi) {
  return ((c >= lo && c <= hi) ? 0x3F80u : 0u) | ((c + 1 >= lo && c + 1 <= hi) ? 0x3F800000u : 0u);
}

__device__ __forceinline__ void conv_far4(uint32_t blk, int lane) {
  const int g = lane >> 2, tq = lane & 3;
  const int c0 = (tq ? 2 * tq - 2 : 14) - g, c2 = 2 * tq + 6 - g;
  const uint32_t n0 = band2(c0, 1, 3), n1 = band2(c0, 4, 8), n2 = band2(c2, 1, 3), n3 = band2(c2, 4, 8);
  uint32_t ua[4][2];
#pragma unroll
  for (int i = 0; i < 4; i++) {
    const int wi = 128 + 4 * (8 * (i - 1) + (g >> 1) + 4 * (g & 1)) + tq;
    ua[i][0] = blk + C_U + word_off(tq ? wi - 4 : wi + 4); ua[i][1] = blk + C_U + word_off(wi);
  }
  const float4 z = lds_f4(blk + C_U);
  uint32_t B[25][2];
#pragma unroll
  for (int f = 0; f < 25; f++) { B[f][0] = lds32(ua[f & 3][0] + (f >> 2) * 512); B[f][1] = lds32(ua[f & 3][1] + (f >> 2) * 512); }
#pragma unroll
  for (int f = 0; f < 25; f++) {
    float d[4];
    mma_bf16_z(d, n0, n1, n2, n3, B[f][0], B[f][1], z);
    B[f][0] = pack_bf16(d[0], d[2]); B[f][1] = pack_bf16(d[1], d[3]);
  }
  float acc[12][4];
  const uint32_t at = blk + C_T2 + 4 * (128 + g - tq);
  uint32_t c1 = 0, c3 = 0;
#pragma unroll
  for (int s = 9; s >= 0; s--) {
    const uint32_t a0 = s == 9 ? lds32(at - 32 * s) : c1 ^ __float_as_uint(z.x), a2 = s == 9 ? lds32(at - 32 * s - 16) : c3 ^ __float_as_uint(z.x);
    const uint32_t a1 = lds32(at - 32 * s + 32), a3 = lds32(at - 32 * s + 16);
    c1 = a1; c3 = a3;
#pragma unroll
    for (int p = 0; p < 12; p++)
      if (s == 9) mma_bf16_z(acc[p], a0, a1, a2, a3, B[s + 2 * p - 7][0], B[s + 2 * p - 7][1], z);
      else if (s + 2 * p - 7 >= 0) mma_bf16(acc[p], a0, a1, a2, a3, B[s + 2 * p - 7][0], B[s + 2 * p - 7][1]);
  }
#pragma unroll
  for (int p = 0; p < 12; p += 2)
    stsm4(blk + C_YF + p * 256 + lane * 16, pack_bf16(acc[p][0], acc[p][1]), pack_bf16(acc[p][2], acc[p][3]),
          pack_bf16(acc[p + 1][0], acc[p + 1][1]), pack_bf16(acc[p + 1][2], acc[p + 1][3]));
}

__device__ __forceinline__ void conv_far8(uint32_t blk, int lane) {
  const int g = lane >> 2, tq = lane & 3;
  const uint32_t n0 = band2(2 * tq - g, 0, 8), n2 = band2(2 * tq + 8 - g, 0, 8), n3 = band2(2 * tq + 8 - g, 9, 15), n5 = band2(2 * tq + 16 - g, 9, 15);
  uint32_t ua[2][4];
#pragma unroll
  for (int i = 0; i < 2; i++)
#pragma unroll
    for (int j = 0; j < 4; j++) ua[i][j] = blk + C_U + word_off(128 + 8 * (8 * i + (g >> 1) + 4 * (g & 1)) - 10 + tq + 4 * j);
  const float4 z = lds_f4(blk + C_U);
  uint32_t n1, n4;
  n1 = lds32(blk + C_U + 16); n4 = lds32(blk + C_U + 36);
  const uint32_t m2 = lds32(blk + C_U + 24), m0 = n2 ^ m2, m1 = n3 ^ m2, m3 = n5 ^ m2, m5 = lds32(blk + C_U + 28), m4 = n0 ^ m5;
  uint32_t B[8][2][2];
#pragma unroll
  for (int s = 0; s < 8; s++) {
    uint32_t w[4];
#pragma unroll
    for (int j = 0; j < 4; j++) w[j] = lds32(ua[s & 1][j] + (s >> 1) * 512);
#pragma unroll
    for (int h = 0; h < 2; h++) {
      float d[4];
      if (h == 0) { mma_bf16_z(d, n0, n1, n2, n3, w[0], w[1], z); mma_bf16_k8(d, n4, n5, w[2]); }
      else { mma_bf16_z(d, m0, m1, m2, m3, w[2], w[3], z); mma_bf16_k8(d, m4, m5, w[1]); }
      B[s][h][0] = pack_bf16(d[0], d[2]); B[s][h][1] = pack_bf16(d[1], d[3]);
    }
  }
  float acc[4][2][4];
  const uint32_t at = blk + C_T3 + 4 * (64 + g - tq);
  uint32_t c1 = 0, c3 = 0;
#pragma unroll
  for (int k = 0; k < 8; k++) {
    const int e = k - 1;
    const uint32_t a0 = k == 0 ? lds32(at + 32 * e) : c1 ^ n1, a2 = k == 0 ? lds32(at + 32 * e - 16) : c3 ^ n1;
    const uint32_t a1 = lds32(at + 32 * e + 32), a3 = lds32(at + 32 * e + 16);
    c1 = a1; c3 = a3;
#pragma unroll
    for (int p = 3; p >= 0; p--)
      if (k == 0) {
        mma_bf16_z(acc[p][0], a0, a1, a2, a3, B[2 * p - e][0][0], B[2 * p - e][0][1], z);
        mma_bf16_z(acc[p][1], a0, a1, a2, a3, B[2 * p - e][1][0], B[2 * p - e][1][1], z);
      } else if (2 * p - e >= 0) {
        mma_bf16(acc[p][0], a0, a1, a2, a3, B[2 * p - e][0][0], B[2 * p - e][0][1]);
        mma_bf16(acc[p][1], a0, a1, a2, a3, B[2 * p - e][1][0], B[2 * p - e][1][1]);
      }
  }
#pragma unroll
  for (int p = 0; p < 4; p++)
    stsm4(blk + C_Y3 + p * 512 + (lane & 15) * 32 + (((lane >> 4) ^ (lane >> 2)) & 1) * 16, pack_bf16(acc[p][0][0], acc[p][0][1]), pack_bf16(acc[p][0][2], acc[p][0][3]),
          pack_bf16(acc[p][1][0], acc[p][1][1]), pack_bf16(acc[p][1][2], acc[p][1][3]));
}

template <bool HI>
__device__ __forceinline__ void conv_final(uint32_t blk, int n, int ch) {
  const uint32_t dsk2 = lds32(blk + C_MISC);
  uint32_t y[4], f[4], uv[4], xv[4];
  const uint32_t co = blk + chunk_off(n);
  lds128(co + C_Y0, y[0], y[1], y[2], y[3]);
  lds128((HI || n >= 36) ? blk + C_Y1 + chunk_off(n - 36) : blk + C_U, f[0], f[1], f[2], f[3]);
  lds128(co + C_U + 512, uv[0], uv[1], uv[2], uv[3]);
  lds128(co + C_X, xv[0], xv[1], xv[2], xv[3]);
  if (HI || n >= 64) {
    uint32_t e[4];
    lds128(blk + C_YF + (n - 64) * 16, e[0], e[1], e[2], e[3]);
    if (HI) {
      const uint32_t kb = lds32(blk + C_T2 + 512) ^ 0x80008000u;
      uint32_t z[4], p[4], q0, q1;
      lds128(blk + C_Y3 + (((n - 128) * 16) ^ ((n << 1) & 16)), z[0], z[1], z[2], z[3]);
      lds128(u_chunk(blk, n - 129), p[0], p[1], p[2], p[3]);
      lds64(co + C_U - 1536, q0, q1);
      z[0] = fma_bf16x2(kb, __byte_perm(p[1], p[2], 0x5432), z[0]); z[1] = fma_bf16x2(kb, __byte_perm(p[2], p[3], 0x5432), z[1]);
      z[2] = fma_bf16x2(kb, __byte_perm(p[3], q0, 0x5432), z[2]); z[3] = fma_bf16x2(kb, __byte_perm(q0, q1, 0x5432), z[3]);
#pragma unroll
      for (int k = 0; k < 4; k++) e[k] = add_bf16x2(e[k], z[k]);
    }
#pragma unroll
    for (int k = 0; k < 4; k++) f[k] = add_bf16x2(f[k], e[k]);
  } else if (n == 63) {
    const float kv = bf_hi(lds32(blk + C_T2 + 256));
    const uint32_t w = lds32(u_chunk(blk, 0));
    f[3] = pack_bf16(fmaf(kv, bf_lo(w), bf_lo(f[3])), fmaf(kv, bf_lo(w) + bf_hi(w), bf_hi(f[3])));
  }
  uint32_t h[4];
#pragma unroll
  for (int k = 0; k < 4; k++) h[k] = add_bf16x2(xv[k], add_bf16x2(add_bf16x2(y[k], f[k]), mul_bf16x2(uv[k], dsk2)));
  ((uint4*)(g_hT + ch * L_SEQ))[n] = make_uint4(h[0], h[1], h[2], h[3]);
}

__device__ __forceinline__ uint32_t opaque_copy2(uint32_t v, uint32_t ident) {
  uint32_t r; asm volatile("mul.lo.u32 %0, %1, %2;" : "=r"(r) : "r"(v), "r"(ident >> 13)); return r;
}
__device__ __forceinline__ uint32_t opaque_copy(uint32_t v, uint32_t ident) {
  uint32_t r; asm volatile("prmt.b32 %0, %1, 0, %2;" : "=r"(r) : "r"(v), "r"(ident)); return r;
}
__device__ __forceinline__ void turn_wait(int w) { asm volatile("bar.sync %0, 256;" ::"r"(9 + w) : "memory"); }
__device__ __forceinline__ void turn_pass(int w) { asm volatile("bar.arrive %0, 256;" ::"r"(10 - w) : "memory"); }

__device__ __forceinline__ void conv_near(uint32_t blk, int wgi, int t, int turns) {
  const int lane = t & 31, ww = t >> 5;
  blk = __shfl_sync(0xffffffffu, blk, 0);
  const uint32_t ident = lds32(blk + C_MISC + 4);
  {
    float nr[32];
    const uint32_t an = blk + ((lane & 4) ? C_PO : C_PE) + 4 * (20 + 144 * (ww >> 1) + 8 * (ww & 1) + (lane >> 3) - (lane & 3));
    uint32_t A[18][4];
    A[0][2] = lds32(an - 16);
#pragma unroll
    for (int n = 0; n < 18; n++) { A[n][0] = lds32(an + n * 32); A[n][1] = lds32(an + n * 32 + 16); }
#pragma unroll
    for (int n = 0; n < 18; n++) {
      if (n) A[n][2] = opaque_copy(A[n - 1][1], ident);
      A[n][3] = opaque_copy2(A[n][0], ident);
    }
    const uint64_t dn = mkdesc(blk + C_U + 512, 16, 512, 2);
    if (turns) named_bar(6, 384);
    if (turns & 1) turn_wait(wgi);
    wg_fence();
#pragma unroll
    for (int n = 0; n < 18; n++) {
      wgmma_rs_n64(nr, A[n][0], A[n][1], A[n][2], A[n][3], dn + (2 * (1 - (n & 1)) - 4 * (n >> 1)), n != 0);
      if (n == 14) wg_commit();
    }
    wg_commit();
    wg_wait<1>();
    if (turns & 2) turn_pass(wgi);
    wg_wait<0>();
    reg_fence<32>(nr);
    const uint32_t st = blk + ((ww >> 1) ? C_Y1 : C_Y0) + chunk_off(4 * ((lane >> 4) * 8 + (lane & 7)) + 2 * (ww & 1) + ((lane >> 3) & 1));
#pragma unroll
    for (int q = 0; q < 4; q++)
      stsm4_t(st + q * 1024, pack_bf16(nr[8 * q], nr[8 * q + 1]), pack_bf16(nr[8 * q + 2], nr[8 * q + 3]),
              pack_bf16(nr[8 * q + 4], nr[8 * q + 5]), pack_bf16(nr[8 * q + 6], nr[8 * q + 7]));
  }
}

struct SsmPtrs { const uint16_t *x, *are, *aim, *bre, *bim, *cre, *cim, *ldt, *dsk; const uint8_t *wg, *wu, *wd; };
__device__ __forceinline__ uint32_t ldg32(const void* p) { uint32_t v; asm volatile("ld.global.nc.u32 %0, [%1];" : "=r"(v) : "l"(p)); return v; }
__device__ __forceinline__ uint16_t ldg16(const void* p) { uint16_t v; asm volatile("ld.global.nc.u16 %0, [%1];" : "=h"(v) : "l"(p)); return v; }
__device__ __forceinline__ RawPair load_pair(const SsmPtrs& P, int ch, int t) {
  const int i = ch * N_STATE + 2 * (t & 63);
  RawPair r;
  r.ldt = ldg16(P.ldt + ch); r.are = ldg32(P.are + i); r.aim = ldg32(P.aim + i); r.bre = ldg32(P.bre + i); r.bim = ldg32(P.bim + i);
  r.cre = ldg32(P.cre + i); r.cim = ldg32(P.cim + i); r.dsk = ldg16(P.dsk + ch);
  return r;
}

struct Ring { int st; uint32_t ph; };
__device__ __forceinline__ void ring_next(Ring& r) { if (++r.st == NSTAGE) { r.st = 0; r.ph ^= 1; } }

template <int I, int N, class F>
__device__ __forceinline__ void static_for(F&& f) {
  if constexpr (I < N) { f(std::integral_constant<int, I>()); static_for<I + 1, N>(f); }
}
struct RingC {
  uint64_t d[2];
  uint32_t b[2], p[2];
  __device__ __forceinline__ uint32_t addr(int s, uint32_t sb) const { return (sb & ~0x3FFFFu) + (((uint32_t)d[(s >> 2) & 1] & 0x3FFF) << 4) + (s & 3) * STAGE_BYTES; }
  __device__ __forceinline__ void wait_full(int s) const { mbar_spin(b[(s >> 2) & 1] + 8 * (s & 3), p[(s >> 2) & 1] ^ ((s >> 3) & 1)); }
  __device__ __forceinline__ void release(int s) const { mbar_arrive(b[(s >> 2) & 1] + 8 * (s & 3) + 8 * (B_EMPTY - B_FULL)); }
  __device__ __forceinline__ void advance12() {
    const uint64_t u = d[0]; d[0] = d[1]; d[1] = u;
    uint32_t t = b[0]; b[0] = b[1]; b[1] = t;
    t = p[0]; p[0] = p[1] ^ 1; p[1] = t;
  }
};
static_assert(NSTAGE == 8 && NST1 == 12 && NST2 == 6 && HEAD > SKEW && HEAD * KS1 <= 16, "RingC");

template <bool HAS_PREV, int S0>
__device__ __forceinline__ void down_step(float* cur, float* prev, uint32_t* H, const RingC& rg,
                                          uint32_t stage_addr, uint32_t stfull_bar, int lane, int w, uint32_t st1, bool remote = false) {
  reg_fence<32>(cur);
  static_for<0, NST2>([&](auto sc) {
    constexpr int s = sc.value;
    static_for<0, KS2>([&](auto kc) {
      constexpr int k = kc.value, kk = 4 * (s * KS2 + k);
      if (k == KS2 - 2) rg.wait_full(S0 + s + 1);
      if ((k & 1) == 0 && (HAS_PREV || s > 0 || k == 0 || k >= 4)) wg_fence();
      wgmma_ring_n64<((S0 + s) & 3) * (STAGE_BYTES / 16) + k * 128, (s | k) != 0>(cur, H[kk], H[kk + 1], H[kk + 2], H[kk + 3], rg.d[((S0 + s) >> 2) & 1]);
      if ((k & 1) == 1 && (HAS_PREV || s > 0 || k >= 3)) wg_commit();
      if (k == 1 && (HAS_PREV || s > 0)) {
        wg_wait<1>();
        if (lane == 0) rg.release(S0 + s - 1);
      }
    });
    if (HAS_PREV && s == 0) {
      reg_fence<32>(prev);
      if (!remote) {
#pragma unroll
        for (int q = 0; q < 4; q++)
          sts128(stage_addr + q * 512, pack_bf16(prev[8 * q], prev[8 * q + 1]), pack_bf16(prev[8 * q + 2], prev[8 * q + 3]),
                 pack_bf16(prev[8 * q + 4], prev[8 * q + 5]), pack_bf16(prev[8 * q + 6], prev[8 * q + 7]));
      } else {
        mbar_wait_cluster(stfull_bar + 8 * (B_PEER - B_IN), 0);
        const uint32_t ra = peer_addr(stage_addr), rb = peer_addr(stfull_bar);
#pragma unroll
        for (int q = 0; q < 4; q++)
          asm volatile("st.async.weak.shared::cluster.mbarrier::complete_tx::bytes.v4.b32 [%0], {%1,%2,%3,%4}, [%5];"
                       ::"r"(ra + q * 512), "r"(pack_bf16(prev[8 * q], prev[8 * q + 1])), "r"(pack_bf16(prev[8 * q + 2], prev[8 * q + 3])),
                         "r"(pack_bf16(prev[8 * q + 4], prev[8 * q + 5])), "r"(pack_bf16(prev[8 * q + 6], prev[8 * q + 7])), "r"(rb) : "memory");
      }
    }
    if (HAS_PREV && s == 1 && !remote) {
      fence_async_smem();
      if (w == 0) {
        asm volatile("bar.arrive %0, 160;" ::"r"(stfull_bar) : "memory");
      } else {
        __syncwarp();
        if (lane == 0) mbar_arrive(st1 + 8 * stfull_bar);
      }
    }
    if (!HAS_PREV && s + 1 < NST2) {
#pragma unroll
      for (int k = 0; k < KS2; k++) {
        const int i = (s + 1) * KS2 + k - 4;
        ldsm4(stage_addr + (i >> 2) * 8192 + (i & 3) * 512, H[16 + 4 * i], H[17 + 4 * i], H[18 + 4 * i], H[19 + 4 * i]);
      }
    }
  });
}

__global__ void __cluster_dims__(2, 1, 1) __launch_bounds__(NTHREADS, 1)
fused_kernel(const __grid_constant__ CUtensorMap tmWg, const __grid_constant__ CUtensorMap tmWu,
             const __grid_constant__ CUtensorMap tmWd, const __grid_constant__ CUtensorMap tmHT,
             const SsmPtrs P, __nv_bfloat16* __restrict__ out) {
  extern __shared__ __align__(1024) uint8_t smem[];
  const uint32_t sb = smem_u32(smem);
  const int mt = blockIdx.x >> 3, fs = blockIdx.x & 7;
  float2* s_r2 = (float2*)(smem + SM_BAR + 2048);
  volatile unsigned* s_epoch = (volatile unsigned*)(smem + SM_BAR + 8 * (B_LN + 1));
  {
    const int tid = threadIdx.x, warp = tid >> 5, lane = tid & 31;
    const int uwarp = __shfl_sync(0xffffffffu, warp, 0);
    const int t = tid & 127;
    const int nch = 5 - (blockIdx.x & 1);
    const bool do_ln = nch == 4;
    const int rb = blockIdx.x >> 1;
    uint4 xr[2][4];
    RawPair m0 = load_pair(P, gch(tid >> 7), t);
    const RawPair m1 = load_pair(P, gch(3 + ((tid >> 7) & 1)), t);
    if (do_ln && tid == 352) {
      mbar_init(sb + SM_BAR + 8 * B_LN, 1);
      mbar_expect_tx(sb + SM_BAR + 8 * B_LN, 64 * D_MODEL);
      fence_async_smem();
      bulk_load(sb + SM_LN, P.x + rb * 32 * D_MODEL, 64 * D_MODEL, sb + SM_BAR + 8 * B_LN);
    }
    const int wgi = uwarp >> 2;
    const bool two = wgi + 3 < nch;
    unsigned ep = 0;
    if (t == 32) ep = __ldcg(&g_epoch);
    if (do_ln) {
      const int g = lane >> 2;
      named_bar(7, 384);
      if (uwarp < 9) {
        mbar_wait(sb + SM_BAR + 8 * B_LN, 0);
        const uint32_t xa = sb + SM_LN + (8 * (lane >> 3) + ((lane >> 2) & 1)) * 2 * D_MODEL + warp * 64 + (lane & 3) * 16;
#pragma unroll
        for (int i = 0; i < 8; i++) {
          uint4& v = xr[i >> 2][i & 3];
          lds128(xa + (i & 3) * 4 * D_MODEL + (i >> 2) * 576, v.x, v.y, v.z, v.w);
        }
#pragma unroll
        for (int i = 0; i < 4; i++) {
          float q[4] = {0, 0, 0, 0};
#pragma unroll
          for (int b = 0; b < 2; b++) {
            mma_bf16(q, xr[b][i].x, 0x3F803F80u, xr[b][i].y, 0x3F803F80u, xr[b][i].x, xr[b][i].y);
            mma_bf16(q, xr[b][i].z, 0x3F803F80u, xr[b][i].w, 0x3F803F80u, xr[b][i].z, xr[b][i].w);
          }
          if ((lane & 3) == (g >> 1))
            sts_f2(sb + SM_LNP + (8 * (g >> 1) + 2 * i + (g & 1)) * 80 + warp * 8, (g & 1) ? q[3] : q[2], (g & 1) ? q[1] : q[0]);
        }
        asm volatile("bar.arrive 4, 320;" ::: "memory");
        uint4* gp = g_xT + (32 * warp + 8 * (g >> 1) + (g & 1)) * 256 + (chunk_off(rb * 4 + (lane & 3)) >> 4);
#pragma unroll
        for (int b = 0; b < 2; b++) {
          st_global(gp + (288 * b + 0) * 256, movm(xr[b][0].x), movm(xr[b][1].x), movm(xr[b][2].x), movm(xr[b][3].x));
          st_global(gp + (288 * b + 2) * 256, movm(xr[b][0].y), movm(xr[b][1].y), movm(xr[b][2].y), movm(xr[b][3].y));
          st_global(gp + (288 * b + 4) * 256, movm(xr[b][0].z), movm(xr[b][1].z), movm(xr[b][2].z), movm(xr[b][3].z));
          st_global(gp + (288 * b + 6) * 256, movm(xr[b][0].w), movm(xr[b][1].w), movm(xr[b][2].w), movm(xr[b][3].w));
        }
        asm volatile("bar.arrive 5, 320;" ::: "memory");
      } else if (warp == 10) {
        named_bar(4, 320);
        const uint32_t pa = sb + SM_LNP + lane * 80;
        const float4 p0 = lds_f4(pa), p1 = lds_f4(pa + 16), p2 = lds_f4(pa + 32), p3 = lds_f4(pa + 48);
        const float2 p4 = lds_f2(pa + 64);
        const float mean = (((p0.x + p0.z) + (p1.x + p1.z)) + ((p2.x + p2.z) + (p3.x + p3.z)) + p4.x) * (1.0f / D_MODEL);
        const float var = fmaxf((((p0.y + p0.w) + (p1.y + p1.w)) + ((p2.y + p2.w) + (p3.y + p3.w)) + p4.y) * (1.0f / D_MODEL) - mean * mean, 0.f);
        float sd;
        asm("sqrt.approx.f32 %0, %1;" : "=f"(sd) : "f"(rbf(rbf(var) + 1e-5f)));
        uint8_t* sp = (uint8_t*)g_stat + (rb * 4 + (lane >> 3)) * 48;
        ((float*)sp)[lane & 7] = rcp_fast(rbf(sd));
        ((uint16_t*)(sp + 32))[lane & 7] = (uint16_t)pack_bf16(mean, 0.f);
        named_bar(5, 320);
        if (lane == 0) asm volatile("red.release.gpu.global.add.u32 [%0], 2;" ::"l"(&g_done[32]) : "memory");
        __syncwarp();
      }
    }
    if (tid == 288) {
      if (sb & 1023) __trap();
#pragma unroll
      for (int i = 0; i < B_COUNT; i++)
        if (i != B_XS)
          mbar_init(sb + SM_BAR + 8 * i, i >= B_MM ? 6 : ((i >= B_EMPTY && i < B_HFULL) || i == B_HFREE || i == B_PRO || i == B_EP) ? 8 : i >= B_PEER ? 4 : 1);
      asm volatile("fence.mbarrier_init.release.cluster;" ::: "memory");
      *s_epoch = ep + 1;
    }
#pragma unroll 1
    for (int i = 0; i <= (int)two; i++) {
      kgen_channel(m0, sb + (wgi + 3 * i) * CHS, sb + SM_QP + (wgi + 3 * i) * 10240, wgi, t, ((wgi + i) & 1) * 64);
      m0 = m1;
    }
    if (wgi == nch - 3) {
      if ((uwarp & 3) == 1) {
        ep = __shfl_sync(0xffffffffu, ep, 0);
        if (elect_one()) {
          mbar_init(sb + SM_BAR + 8 * B_XS, 1);
          fence_async_smem();
          mbar_expect_tx(sb + SM_BAR + 8 * B_XS, 4096 * nch + 12288);
          wait_flag(&g_done[32], (ep + 1) * NCTA);
          fence_async_global();
          bulk_load(sb + SM_STAT, g_stat, 12288, sb + SM_BAR + 8 * B_XS);
#pragma unroll
          for (int c = 0; c < 5; c++)
            if (c < nch) bulk_load(sb + c * CHS + C_X, g_xT + gch(c) * 256, 4096, sb + SM_BAR + 8 * B_XS);
        }
        __syncwarp();
      }
      if ((warp & 3) == 2 && lane < 4)
        asm volatile("prefetch.tensormap [%0];" ::"l"(lane == 0 ? &tmWg : lane == 1 ? &tmWu : lane == 2 ? &tmWd : &tmHT) : "memory");
      wg_bar(wgi);
      mbar_wait_long(sb + SM_BAR + 8 * B_XS, 0);
      float4 r[2][2];
      uint32_t mm[2][4];
#pragma unroll
      for (int h = 0; h < 2; h++) {
        const uint32_t sa = sb + SM_STAT + (t + 128 * h) * 48;
        r[h][0] = lds_f4(sa); r[h][1] = lds_f4(sa + 16);
        lds128(sa + 32, mm[h][0], mm[h][1], mm[h][2], mm[h][3]);
      }
      const uint32_t co = sb + chunk_off(t);
#pragma unroll
      for (int c = 0; c < 5; c++) {
        if (c < nch) {
#pragma unroll
          for (int h = 0; h < 2; h++) {
            uint32_t x[4];
            lds128(co + c * CHS + C_X + h * 2048, x[0], x[1], x[2], x[3]);
#pragma unroll
            for (int q = 0; q < 4; q++) x[q] = sub_bf16x2(x[q], mm[h][q]);
            sts128(co + c * CHS + C_U + 512 + h * 2048, pack_bf16(bf_lo(x[0]) * r[h][0].x, bf_hi(x[0]) * r[h][0].y),
                   pack_bf16(bf_lo(x[1]) * r[h][0].z, bf_hi(x[1]) * r[h][0].w), pack_bf16(bf_lo(x[2]) * r[h][1].x, bf_hi(x[2]) * r[h][1].y),
                   pack_bf16(bf_lo(x[3]) * r[h][1].z, bf_hi(x[3]) * r[h][1].w));
          }
        }
        if (c == 1 && nch == 5) { fence_async_smem(); asm volatile("bar.arrive 6, 384;" ::: "memory"); }
      }
    }
    fence_async_smem();
    if (wgi < 2 && nch == 5) asm volatile("bar.arrive 8, 384;" ::: "memory");
    if (wgi == 2) {
      if (nch == 5) named_bar(8, 384); else named_bar(6, 384);
      if (uwarp == 11) {
        if (lane < HBOX8_STAGE) mbar_expect_tx(sb + SM_BAR + 8 * (B_FULL + lane), STAGE_BYTES);
        else if (lane >= 8 && lane < 26) mbar_expect_tx(sb + SM_BAR + 8 * (B_HFULL + lane - 8), 8192);
        if (elect_one()) {
#pragma unroll
          for (int i = 0; i < 2 * HBOX8_STAGE; i++)
            tma_load_2d(sb + SM_RING + i * (STAGE_BYTES / 2), (i & 1) ? &tmWu : &tmWg, fs * 576 + 64, (i >> 1) * KS1 * 16,
                        sb + SM_BAR + 8 * (B_FULL + (i >> 1)));
        }
        __syncwarp();
      }
    }
    if (wgi < 2) {
      const int nnear = (nch == 5 && wgi == 0) ? 3 : 2;
#pragma unroll 1
      for (int i = 0; i < nnear; i++) {
        const int c = i == 2 ? 2 : wgi == 0 ? 3 * i : (i == 0 ? 1 : nch == 5 ? 4 : 2);
        conv_near(sb + c * CHS, wgi, t, i == 0 ? 2 - wgi : 0);
        __syncwarp();
        if (lane == 0) mbar_arrive(sb + SM_BAR + 8 * (B_MM + c));
        if (i < 2) {
          mbar_wait_long(sb + SM_BAR + 8 * (B_MM + c), 0);
          conv_final<false>(sb + c * CHS, t, gch(c));
          conv_final<true>(sb + c * CHS, t + 128, gch(c));
          if (i == 0) {
            fence_async_smem();
            __syncwarp();
            if (lane == 0) mbar_arrive(sb + SM_BAR + 8 * B_EP);
          }
        }
      }
    } else {
      uint32_t tasks = nch == 5 ? (uwarp == 8 ? 0xF80u : uwarp == 9 ? 0xF972u : uwarp == 10 ? 0xF431u : 0xF5E6u)
                                : (uwarp == 8 ? 0xFE70u : uwarp == 9 ? 0xF52u : uwarp == 10 ? 0xF61u : 0xF43u);
#pragma unroll 1
      for (; (tasks & 15) != 15; tasks >>= 4) {
        const int c = (tasks & 15) >> 1;
        if (c == 7) {
          if (lane == 0) {
            mbar_wait_long(sb + SM_BAR + 8 * B_EP, 0);
            asm volatile("red.release.gpu.global.add.u32 [%0], 1;" ::"l"(&g_done[64]) : "memory");
          }
          __syncwarp();
          continue;
        }
        if (tasks & 1) conv_far8(sb + c * CHS, lane); else conv_far4(sb + c * CHS, lane);
        if (c < 2) fence_async_smem();
        __syncwarp();
        if (lane == 0) mbar_arrive(sb + SM_BAR + 8 * (B_MM + c));
      }
      if (uwarp == 8) {
        fence_async_smem();
        asm volatile("bar.arrive 0, 384;" ::: "memory");
        if (elect_one()) {
          wait_flag(&g_done[64], *s_epoch * NCTA);
          fence_async_global();
#pragma unroll
          for (int j = 0; j < 4; j++)
            tma_load_2d_pair(sb + hbox_off(fs & 1, j), &tmHT, mt * 128 + (fs & 1) * 64, j * 64, sb + SM_BAR + 8 * (B_HFULL + 9 * (fs & 1) + j));
        }
        __syncwarp();
      }
    }
    if (nch == 5 && wgi != 2) {
      mbar_wait_long(sb + SM_BAR + 8 * (B_MM + 2), 0);
      if (wgi) conv_final<true>(sb + 2 * CHS, t + 128, gch(2)); else conv_final<false>(sb + 2 * CHS, t, gch(2));
    }
    fence_async_smem();
    asm volatile("{\n.reg .pred p, q;\nsetp.eq.s32 p, %0, 9;\nsetp.ne.and.s32 q, %0, 8, !p;\n@p bar.sync 0, 384;\n@q bar.arrive 0, 384;\n}\n" ::"r"(uwarp) : "memory");
    __syncwarp();
    if (wgi < 2) {
      float csum[32];
      const uint64_t d0 = mkdesc(__shfl_sync(0xffffffffu, sb + SM_RING + wgi * (STAGE_BYTES / 2), 0), 0, 1024, 1);
#pragma unroll
      for (int s = 0; s < HEAD; s++) mbar_spin(sb + SM_BAR + 8 * (B_FULL + s), 0);
      wg_fence();
      static_for<0, HEAD * KS1>([&](auto ic) {
        wgmma_ring_n64<(ic.value / KS1) * (STAGE_BYTES / 16) + (ic.value % KS1) * 128, ic.value != 0>(csum, 0x3F803F80u, 0x3F803F80u, 0x3F803F80u, 0x3F803F80u, d0);
      });
      wg_commit();
      wg_wait<0>();
      reg_fence<32>(csum);
      if (t < 4) {
#pragma unroll
        for (int j = 0; j < 8; j++) {
          const uint32_t hi = pack_bf16(csum[4 * j], csum[4 * j + 1]);
          sts32(sb + SM_CS + wgi * 256 + j * 32 + t * 4, hi);
          sts32(sb + SM_CS + wgi * 256 + j * 32 + 16 + t * 4, pack_bf16(csum[4 * j] - bf_lo(hi), csum[4 * j + 1] - bf_hi(hi)));
        }
      } else if (t < 28) {
        sts32(sb + SM_CS + 512 + (t - 4) * 4, 0);
      }
      if (t < 32) fence_async_smem();
      __syncwarp();
    }
  }
  int tid;
  asm volatile("mov.u32 %0, %%tid.x;" : "=r"(tid));
  const int warp = tid >> 5, lane = tid & 31, uwarp = __shfl_sync(0xffffffffu, warp, 0);
  const unsigned epoch = *s_epoch;

  if (uwarp >= 8) {
    asm volatile("setmaxnreg.dec.sync.aligned.u32 24;");
    if (tid == 288) asm volatile("red.release.gpu.global.add.u32 [%0], 1;" ::"l"(&g_done[0]) : "memory");
    if (uwarp == 8) {
      if (elect_one()) {
        wait_flag(&g_done[0], epoch * NCTA);
        fence_async_global();
#pragma unroll
        for (int j = 4; j < 9; j++)
          tma_load_2d_pair(sb + hbox_off(fs & 1, j), &tmHT, mt * 128 + (fs & 1) * 64, j * 64, sb + SM_BAR + 8 * (B_HFULL + 9 * (fs & 1) + j));
        if (blockIdx.x == 0) *(volatile unsigned*)&g_epoch = epoch;
        mbar_wait(sb + SM_BAR + 8 * B_HFREE, 0);
        Ring rg{HBOX8_STAGE, 1};
#pragma unroll 1
        for (int c = 0; c < 9; c++)
#pragma unroll 1
          for (int s = c ? 0 : HBOX8_STAGE; s < NST1; s++) {
            {
              mbar_wait(sb + SM_BAR + 8 * (B_EMPTY + rg.st), rg.ph);
              const uint32_t bar = sb + SM_BAR + 8 * (B_FULL + rg.st), dst = sb + SM_RING + rg.st * STAGE_BYTES;
              mbar_expect_tx(bar, STAGE_BYTES);
              tma_load_2d(dst, &tmWg, fs * 576 + (c == 8 ? 0 : c + 1) * 64, s * KS1 * 16, bar);
              tma_load_2d(dst + STAGE_BYTES / 2, &tmWu, fs * 576 + (c == 8 ? 0 : c + 1) * 64, s * KS1 * 16, bar);
            }
            ring_next(rg);
          }
#pragma unroll 1
        for (int c = 0; c < 9; c++) {
          const int ch = step_chunk(fs, c);
#pragma unroll 1
          for (int s = 0; s < NST2; s++) {
            mbar_wait(sb + SM_BAR + 8 * (B_EMPTY + rg.st), rg.ph);
            const uint32_t bar = sb + SM_BAR + 8 * (B_FULL + rg.st), dst = sb + SM_RING + rg.st * STAGE_BYTES;
            mbar_expect_tx(bar, STAGE_BYTES);
            tma_load_2d(dst, &tmWd, ch * 64, fs * 576 + s * KS2 * 16, bar);
            ring_next(rg);
          }
        }
#pragma unroll 1
        for (int w = 0; w < 3; w++) {
          mbar_wait(sb + SM_BAR + 8 * (B_EMPTY + rg.st), rg.ph);
          const uint32_t bar = sb + SM_BAR + 8 * (B_FULL + rg.st), dst = sb + SM_RING + rg.st * STAGE_BYTES;
          mbar_expect_tx(bar, 8192);
          tma_load_2d(dst, &tmHT, mt * 128 + (w == 0 ? fs >> 2 : w - 1) * 64, w == 0 ? 512 : fs * 64, bar);
          ring_next(rg);
        }
      }
    } else {
      if (uwarp < 11) {
        const int w = uwarp - 9;
        mbar_wait_long(sb + SM_BAR + 8 * (B_HFULL + w * 9 + fs + 1), 0);
        float q0 = 0.f, q1 = 0.f;
#pragma unroll 1
        for (uint32_t a = sb + hbox_off(w, fs + 1), e = a + 8192; a < e; a += 1024) {
#pragma unroll
          for (int d = 0; d < 8; d++) {
            const uint32_t v = lds32(a + d * 128 + ((lane * 4) ^ (d << 4)));
            q0 = fmaf(bf_lo(v), bf_lo(v), q0); q1 = fmaf(bf_hi(v), bf_hi(v), q1);
          }
        }
        __syncwarp();
        if (lane == 0) mbar_arrive(sb + SM_BAR + 8 * (B_SQ + w));
        uint2* sq = g_sq + (mt * 128 + w * 64 + 2 * lane) * 8 + fs;
        const uint64_t tag = (uint64_t)epoch << 32;
        asm volatile("st.relaxed.gpu.global.u64 [%0], %1;" ::"l"(sq), "l"(tag | __float_as_uint(q0)) : "memory");
        asm volatile("st.relaxed.gpu.global.u64 [%0], %1;" ::"l"(sq + 8), "l"(tag | __float_as_uint(q1)) : "memory");
      } else {
        mbar_wait_long(sb + SM_BAR + 8 * B_PRO, 0);
#pragma unroll 1
        for (int row = lane; row < 128; row += 32) {
          float sq = 0.f;
#pragma unroll 1
          for (int k = 0; k < 4; k++) {
            uint64_t v0, v1;
            int it = 0;
            do {
              asm volatile("ld.relaxed.gpu.global.v2.u64 {%0,%1}, [%2];" : "=l"(v0), "=l"(v1) : "l"(g_sq + (mt * 128 + row) * 8 + 2 * k) : "memory");
              asm volatile("{\n.reg .pred q;\nsetp.gt.s32 q, %0, 4194304;\n@q trap;\n}" ::"r"(++it));
            } while ((uint32_t)(v0 >> 32) != epoch || (uint32_t)(v1 >> 32) != epoch);
            sq += __uint_as_float((uint32_t)v0) + __uint_as_float((uint32_t)v1);
          }
          const float2 loc = s_r2[row];
          float sd;
          asm("sqrt.approx.f32 %0, %1;" : "=f"(sd) : "f"(rbf(rbf(fmaxf(fmaf(sq, 1.0f / D_MODEL, loc.x), 0.f)) + 1e-5f)));
          const float f = rcp_fast(rbf(sd) * loc.y);
          s_r2[row].x = f * f;
        }
        __syncwarp();
        if (lane == 0) mbar_expect_tx(sb + SM_BAR + 8 * B_C8, 16384);
      }
      if (lane == 0) mbar_expect_tx(sb + SM_BAR + 8 * (B_IN + uwarp - 9), uwarp == 11 ? 2 * 8192 : 6 * 8192);
#pragma unroll 1
      for (int s = uwarp - 9; s < 7; s += 3) {
        asm volatile("bar.sync %0, 160;" ::"r"(7 + s) : "memory");
        if (elect_one()) {
          const int slot = (mt * 9 + step_chunk(fs, s)) * 8 + fs;
          const uint32_t sa = sb + SM_PARK + s * 8192;
          bulk_store(g_part + (size_t)slot * 1024, sa, 8192);
          mbar_wait(sb + SM_BAR + 8 * (B_ST1 + s), 0);
          bulk_store(g_part + (size_t)slot * 1024 + 512, sa + 65536, 8192);
          bulk_commit();
          bulk_wait0();
          st_release(&g_flag[slot], epoch);
          if (s > 0) {
            const int in = (mt * 9 + fs) * 8 + (fs ^ (8 - s));
            wait_flag(&g_flag[in], epoch);
            fence_async_global();
            bulk_load(sa, g_part + (size_t)in * 1024, 8192, sb + SM_BAR + 8 * (s == 6 ? B_IN6 : B_IN));
            bulk_load(sa + 65536, g_part + (size_t)in * 1024 + 512, 8192, sb + SM_BAR + 8 * (s == 6 ? B_IN6 : B_IN + 1));
          }
        }
        __syncwarp();
      }
      __syncwarp();
      if (uwarp == 10) {
        const int base = (mt * 9 + 8) * 16;
        if (lane < 8) wait_flag(&g_flag[(mt * 9 + 8) * 8 + lane], epoch);
        __syncwarp();
        if (lane < 8) {
          fence_async_global();
          bulk_load(sb + SM_PARK + (lane >> 2) * 65536 + (lane & 3) * 2048,
                    g_part + (size_t)(base + lane * 2 + (fs >> 2)) * 512 + (fs & 3) * 128, 2048, sb + SM_BAR + 8 * B_C8);
        }
      }
    }
  } else {
    asm volatile("setmaxnreg.inc.sync.aligned.u32 240;");
    const int w = uwarp >> 2, ww = uwarp & 3, g = lane >> 2;
    const uint32_t park = sb + SM_PARK + w * 65536 + ww * 2048 + lane * 16;
    const uint32_t lm_off = ((lane & 7) + ((lane >> 4) << 3)) * 128 + (((2 * ww + ((lane >> 3) & 1)) ^ (lane & 7)) << 4);
    RingC rg;
    rg.d[0] = mkdesc(sb + SM_RING, STAGE_BYTES / 2, 1024, 1); rg.d[1] = rg.d[0] + 4 * STAGE_BYTES / 16;
    rg.b[0] = sb + SM_BAR + 8 * B_FULL; rg.b[1] = rg.b[0] + 32;
    rg.p[0] = rg.p[1] = 0;
    uint32_t X[144], H[144];
    {
      float acc[64];
      constexpr int HK = HEAD * KS1;
      float sA[4] = {0, 0, 0, 0};
      uint32_t pp0, pp1;
      auto load_box = [&](auto jc) {
        constexpr int j = jc.value;
        mbar_spin(sb + SM_BAR + 8 * (B_HFULL + w * 9 + j), 0);
        const uint32_t box = sb + hbox_off(w, j) + lm_off;
#pragma unroll
        for (int k = 0; k < 4; k++) {
          uint32_t* x = X + 16 * j + 4 * k;
          ldsm4_t(box + k * 2048, x[0], x[1], x[2], x[3]);
        }
#pragma unroll
        for (int k = 0; k < 4; k++) {
          uint32_t* x = X + 16 * j + 4 * k;
          mma_bf16(sA, x[0], x[1], x[2], x[3], 0x3F803F80u, 0x3F803F80u);
        }
      };
      constexpr int HB = (HK + 3) / 4;
      static_for<0, HB>([&](auto jc) {
        load_box(jc);
        if (jc.value == 0) {
          if (lane == 0) mbar_arrive(sb + SM_BAR + 8 * B_HFREE);
          float qa[4] = {0, 0, 0, 0}, qb[4] = {0, 0, 0, 0};
#pragma unroll
          for (int k = 0; k < 4; k++) {
            uint32_t* x = X + 4 * k;
            mma_bf16(qa, x[0], x[1], x[2], x[3], x[0], x[2]);
            mma_bf16(qb, x[0], x[1], x[2], x[3], x[1], x[3]);
          }
          const float d0 = __shfl_sync(0xffffffffu, (g & 1) ? qa[1] : qa[0], g * 4 + (g >> 1));
          const float d1 = __shfl_sync(0xffffffffu, (g & 1) ? qb[3] : qb[2], g * 4 + (g >> 1));
          const float p0 = __uint_as_float((190u - (__float_as_uint(fmaf(d0, 1.0f / 64, 1e-5f)) >> 24)) << 23);
          const float p1 = __uint_as_float((190u - (__float_as_uint(fmaf(d1, 1.0f / 64, 1e-5f)) >> 24)) << 23);
          pp0 = pack_bf16(p0, p0); pp1 = pack_bf16(p1, p1);
          if ((lane & 3) == 0) {
            s_r2[w * 64 + ww * 16 + g] = make_float2(d0 * (1.0f / D_MODEL), p0);
            s_r2[w * 64 + ww * 16 + g + 8] = make_float2(d1 * (1.0f / D_MODEL), p1);
          }
        }
      });
#pragma unroll
      for (int i = 0; i < 4 * HK; i++) H[i] = mul_bf16x2(X[i], (i & 1) ? pp1 : pp0);
      wg_fence();
      static_for<0, HK>([&](auto ic) {
        constexpr int s = ic.value / KS1, k = ic.value % KS1, kk = 4 * ic.value;
        wgmma_ring_n128<(s & 3) * (STAGE_BYTES / 16) + k * 128, ic.value != 0>(acc, H[kk], H[kk + 1], H[kk + 2], H[kk + 3], rg.d[(s >> 2) & 1]);
      });
      wg_commit();
      static_for<HB, 9>([&](auto jc) {
        if (jc.value == 4) {
          wg_wait<0>();
          if (lane == 0) static_for<0, HEAD - 1>([&](auto sc) { rg.release(sc.value); });
        }
        load_box(jc);
      });
      const float m0 = sA[0] * (1.0f / D_MODEL), m1 = sA[2] * (1.0f / D_MODEL);
      const uint32_t mm0 = mul_bf16x2(pack_bf16(-m0, -m0), pp0), mm1 = mul_bf16x2(pack_bf16(-m1, -m1), pp1);
      if ((lane & 3) == 0) {
        s_r2[w * 64 + ww * 16 + g].x -= m0 * m0;
        s_r2[w * 64 + ww * 16 + g + 8].x -= m1 * m1;
      }
      __syncwarp();
      if (lane == 0) mbar_arrive(sb + SM_BAR + 8 * B_PRO);
      mbar_spin(sb + SM_BAR + 8 * B_HFREE, 0);
      {
        const uint32_t cm0 = (lane & 3) ? 0u : mm0, cm1 = (lane & 3) ? 0u : mm1;
        reg_fence<64>(acc);
        wg_fence();
        wgmma_ring_n128<0, 1>(acc, cm0, cm1, 0u, 0u, mkdesc(sb + SM_CS, 0, 32, 0));
        wg_commit();
      }
      if (w == 1) named_bar(5, 256);
#pragma unroll
      for (int i = 0; i < 144; i++) X[i] = fma_bf16x2(X[i], (i & 1) ? pp1 : pp0, (i & 1) ? mm1 : mm0);
      wg_wait<0>();
      rg.wait_full(HEAD);
#pragma unroll 1
      for (int c = 0;; c++) {
        reg_fence<64>(acc);
        if ((w | c) == 0) named_bar(5, 256);
        if (w == 1) named_bar(4, 256);
        auto kstep = [&](auto ic) {
          constexpr int s = ic.value / KS1, k = ic.value % KS1, kk = 4 * ic.value;
          if (s == SKEW && k == 0 && w == 0) asm volatile("bar.arrive 4, 256;" ::: "memory");
          if (s == HEAD + SKEW && k == 0 && (w | c) == 0) asm volatile("bar.arrive 4, 256;" ::: "memory");
          if (k == KS1 - 1) rg.wait_full(s + 1);
          wg_fence();
          wgmma_ring_n128<(s & 3) * (STAGE_BYTES / 16) + k * 128, (s | k) != 0>(acc, X[kk], X[kk + 1], X[kk + 2], X[kk + 3], rg.d[(s >> 2) & 1]);
          wg_commit();
          if (k == 0 && s > 0) {
            wg_wait<1>();
            if (lane == 0) rg.release(s - 1);
          }
        };
        if (c > 0) static_for<0, HK>(kstep);
        static_for<HK, 36>(kstep);
        wg_wait<0>();
        if (lane == 0) rg.release(NST1 - 1);
        rg.advance12();
        reg_fence<64>(acc);
        if (c == 8) break;
        if (c == 0) { mbar_spin(sb + SM_BAR + 8 * B_SQ, 0); mbar_spin(sb + SM_BAR + 8 * (B_SQ + 1), 0); }
#pragma unroll
        for (int q = 0; q < 16; q++)
          asm volatile("stmatrix.sync.aligned.m8n8.x1.shared.b16 [%0], {%1};" ::"r"(park + c * 8192 + q * 128), "r"(reglu2(acc + 2 * q)) : "memory");
      }
#pragma unroll
      for (int i = 0; i < 16; i++) H[i] = reglu2(acc + 2 * i);
#pragma unroll
      for (int i = 0; i < KS2 - 4; i++) ldsm4(park + (i >> 2) * 8192 + (i & 3) * 512, H[16 + 4 * i], H[17 + 4 * i], H[18 + 4 * i], H[19 + 4 * i]);
    }
    float a0[32], a1[32];
    const uint32_t st1 = sb + SM_BAR + 8 * (B_ST1 - 7);
    down_step<false, 0>(a0, a1, H, rg, park, 0, lane, w, 0);
    if (lane == 0) mbar_arrive_peer(sb + SM_BAR + 8 * (B_PEER + w));
#pragma unroll 1
    for (int p = 0; p < 4; p++) {
      down_step<true, 6>(a1, a0, H, rg, park + (2 * p) * 8192, 7 + 2 * p, lane, w, st1);
      down_step<true, 12>(a0, a1, H, rg, park + (2 * p + 1) * 8192, p == 3 ? sb + SM_BAR + 8 * (B_IN + w) : 8 + 2 * p, lane, w, st1, p == 3);
      rg.advance12();
    }
    wg_wait<0>();
    reg_fence<32>(a0);
    const uint32_t eye = (g >> 1) == (lane & 3) ? ((g & 1) ? 0x3F800000u : 0x3F80u) : 0u;
    mbar_wait(sb + SM_BAR + 8 * B_C8, 0);
    mbar_wait(sb + SM_BAR + 8 * (B_IN + w), 0);
    if (w == 0) rg.wait_full(7); else rg.wait_full(8);
    float c8[4] = {0, 0, 0, 0};
    uint32_t h0, h1;
#pragma unroll
    for (int src = 0; src < 8; src++)
      lds64(sb + SM_PARK + (src >> 2) * 65536 + (src & 3) * 2048 + (warp >> 1) * 512 + lane * 16 + (warp & 1) * 8, H[128 + 2 * src], H[129 + 2 * src]);
#pragma unroll
    for (int i = 0; i < 24; i++)
      lds128(park + (i < 20 ? 1 + (i >> 2) : 7) * 8192 + (i & 3) * 512, H[16 + 4 * i], H[17 + 4 * i], H[18 + 4 * i], H[19 + 4 * i]);
    asm volatile("ldmatrix.sync.aligned.m8n8.x2.trans.shared.b16 {%0,%1}, [%2];" : "=r"(h0), "=r"(h1)
                 : "r"(rg.addr(6, sb) + (8 * warp + (lane & 7)) * 128 + (((2 * (fs & 3) + ((lane >> 3) & 1)) ^ (lane & 7)) << 4)) : "memory");
    const uint32_t hb = w == 0 ? rg.addr(7, sb) : rg.addr(8, sb);
#pragma unroll
    for (int k = 0; k < 4; k++) ldsm4_t(hb + lm_off + k * 2048, H[4 * k], H[4 * k + 1], H[4 * k + 2], H[4 * k + 3]);
    const float r2a = s_r2[w * 64 + ww * 16 + g].x, r2b = s_r2[w * 64 + ww * 16 + g + 8].x;
    const float ra = s_r2[fs * 16 + g].x, rb = s_r2[fs * 16 + g + 8].x;
#pragma unroll
    for (int i = 0; i < 48; i++) {
      if (i % 5 == 0 && i < 40) mma_bf16_k8(c8, H[128 + 2 * (i / 5)], H[129 + 2 * (i / 5)], eye);
      mma_bf16_k8(a0 + 4 * (i & 7), H[16 + 2 * i], H[17 + 2 * i], eye);
    }
    uint32_t* o8 = (uint32_t*)(out + (size_t)(mt * 128 + fs * 16 + g) * D_MODEL + 512 + warp * 8 + 2 * (lane & 3));
    o8[0] = pack_bf16(fmaf(c8[0], ra, bf_lo(h0)), fmaf(c8[1], ra, bf_hi(h0)));
    o8[8 * D_MODEL / 2] = pack_bf16(fmaf(c8[2], rb, bf_lo(h1)), fmaf(c8[3], rb, bf_hi(h1)));
    mbar_wait(sb + SM_BAR + 8 * B_IN6, 0);
#pragma unroll
    for (int i = 24; i < 28; i++) lds128(park + 6 * 8192 + (i & 3) * 512, H[16 + 4 * i], H[17 + 4 * i], H[18 + 4 * i], H[19 + 4 * i]);
#pragma unroll
    for (int i = 48; i < 56; i++) mma_bf16_k8(a0 + 4 * (i & 7), H[16 + 2 * i], H[17 + 2 * i], eye);
#pragma unroll
    for (int j = 0; j < 16; j++)
      H[j] = pack_bf16(fmaf(a0[2 * j], (j & 1) ? r2b : r2a, bf_lo(H[j])), fmaf(a0[2 * j + 1], (j & 1) ? r2b : r2a, bf_hi(H[j])));
    const uint32_t ob = sb + SM_PARK + w * 65536 + 8192 + ww * 2048;
    __syncwarp();
#pragma unroll
    for (int k = 0; k < 4; k++)
      stsm4(ob + (lane & 15) * 128 + (((2 * k + (lane >> 4)) ^ (lane & 7)) << 4), H[4 * k], H[4 * k + 1], H[4 * k + 2], H[4 * k + 3]);
    __syncwarp();
    uint4* o = (uint4*)(out + (size_t)(mt * 128 + w * 64 + ww * 16 + (lane >> 3)) * D_MODEL + fs * 64) + (lane & 7);
#pragma unroll
    for (int k = 0; k < 4; k++) {
      uint4 v;
      lds128(ob + (4 * k + (lane >> 3)) * 128 + (((lane & 7) ^ ((4 * k + (lane >> 3)) & 7)) << 4), v.x, v.y, v.z, v.w);
      o[k * 4 * (D_MODEL / 8)] = v;
    }
  }
}

typedef CUresult (*EncodeFn)(CUtensorMap*, CUtensorMapDataType, cuuint32_t, void*, const cuuint64_t*, const cuuint64_t*,
                             const cuuint32_t*, const cuuint32_t*, CUtensorMapInterleave, CUtensorMapSwizzle,
                             CUtensorMapL2promotion, CUtensorMapFloatOOBfill);
static void make_map(EncodeFn enc, CUtensorMap* m, const void* ptr, uint64_t cols, uint64_t rows, uint32_t bc, uint32_t br,
                     CUtensorMapSwizzle swz) {
  cuuint64_t dims[2] = {cols, rows};
  cuuint64_t strides[1] = {cols * 2};
  cuuint32_t box[2] = {bc, br};
  cuuint32_t es[2] = {1, 1};
  enc(m, CU_TENSOR_MAP_DATA_TYPE_BFLOAT16, 2, (void*)ptr, dims, strides, box, es, CU_TENSOR_MAP_INTERLEAVE_NONE, swz,
      CU_TENSOR_MAP_L2_PROMOTION_L2_128B, CU_TENSOR_MAP_FLOAT_OOB_FILL_NONE);
}

extern "C" void kernel_launch(void* const* d_in, const int* in_sizes, int n_in, void* d_out, int out_size) {
  static EncodeFn enc = nullptr;
  static void* hT = nullptr;
  if (!enc) {
    void* fn = nullptr; cudaDriverEntryPointQueryResult qr;
    cudaGetDriverEntryPoint("cuTensorMapEncodeTiled", &fn, cudaEnableDefault, &qr);
    enc = (EncodeFn)fn;
    cudaGetSymbolAddress(&hT, g_hT);
    cudaFuncSetAttribute(fused_kernel, cudaFuncAttributeMaxDynamicSharedMemorySize, SMEM_BYTES);
  }
  CUtensorMap tmWg, tmWu, tmWd, tmHT;
  make_map(enc, &tmWg, d_in[10], F_FFN, D_MODEL, 64, KS1 * 16, CU_TENSOR_MAP_SWIZZLE_128B);
  make_map(enc, &tmWu, d_in[11], F_FFN, D_MODEL, 64, KS1 * 16, CU_TENSOR_MAP_SWIZZLE_128B);
  make_map(enc, &tmWd, d_in[12], D_MODEL, F_FFN, 64, KS2 * 16, CU_TENSOR_MAP_SWIZZLE_128B);
  make_map(enc, &tmHT, hT, L_SEQ, D_MODEL, 64, 64, CU_TENSOR_MAP_SWIZZLE_128B);
  typedef const uint16_t* up;
  SsmPtrs P{(up)d_in[0], (up)d_in[1], (up)d_in[2], (up)d_in[3], (up)d_in[4], (up)d_in[5], (up)d_in[6], (up)d_in[7], (up)d_in[8],
            (const uint8_t*)d_in[10], (const uint8_t*)d_in[11], (const uint8_t*)d_in[12]};
  fused_kernel<<<NCTA, NTHREADS, SMEM_BYTES>>>(tmWg, tmWu, tmWd, tmHT, P, (__nv_bfloat16*)d_out);
}
```
